```python
import torch

def _softmax(x, axis=-1):
    return torch.softmax(x, dim=axis)
def _gelu(x):
    return torch.nn.functional.gelu(x, approximate="tanh")
def _silu(x):
    return torch.nn.functional.silu(x)
def _sigmoid(x):
    return torch.sigmoid(x)
def _layernorm(x, axis=-1, eps=1e-5):
    m = x.mean(dim=axis, keepdim=True)
    v = x.var(dim=axis, keepdim=True, unbiased=False)
    return (x - m) / torch.sqrt(v + eps)
def _scatter_add(tgt, idx, src, axis=0):
    return tgt.clone().index_add_(axis, idx, src)
def _segment_sum(src, seg, n):
    out = torch.zeros((n,) + src.shape[1:], dtype=src.dtype)
    return out.index_add_(0, seg, src)
def _pad(x, pw):
    flat = tuple(v for pair in reversed(pw) for v in pair)
    return torch.nn.functional.pad(x, flat)

kernel_name = 'gated_mix__compressed_kv_cla__dense_activation_silu__decode'

def setup_inputs():

    _w = (lambda a: (lambda t: t.to(torch.bfloat16) if t.is_floating_point() else t)(torch.as_tensor(a)))
    def _A_setup():
        B, H, Sq, Sk, D, M = 1, 32, 1, 4096, 128, 640
        Dc = 4 * D
        return {
            "x": _w((lambda *s: torch.randn(*s, dtype=torch.bfloat16) * 0.05)(B, Sq, M)),
            "c_kv": _w((lambda *s: torch.randn(*s, dtype=torch.bfloat16) * 0.2)(B, Sk, Dc)),
            "w_q": _w((lambda *s: torch.randn(*s, dtype=torch.bfloat16) * 3.2)(M, H, D) * (M ** -0.5)),
            "w_uk": _w((lambda *s: torch.randn(*s, dtype=torch.bfloat16) * 3.2)(Dc, H, D) * (Dc ** -0.5)),
            "w_uv": _w((lambda *s: torch.randn(*s, dtype=torch.bfloat16) * 0.2)(Dc, H, D) * (Dc ** -0.5)),
            "w_o": _w((lambda *s: torch.randn(*s, dtype=torch.bfloat16) * 0.2)(H, D, M) * ((H * D) ** -0.5)),
        }
    _A_in = _A_setup()

    def _B_setup():
        B, S, D, F = 1, 1, 640, 1728
        return {
            "x": _w((lambda *s: torch.randn(*s, dtype=torch.bfloat16) * 0.05)(B, S, D)),
            "w1": _w((lambda *s: torch.randn(*s, dtype=torch.bfloat16) * 0.05)(D, F) * (D ** -0.5)),
            "w2": _w((lambda *s: torch.randn(*s, dtype=torch.bfloat16) * 0.05)(F, D) * (F ** -0.5)),
        }
    _B_in = _B_setup()

    return {
        "A_x": _A_in["x"],
        "A_c_kv": _A_in["c_kv"],
        "A_w_q": _A_in["w_q"],
        "A_w_uk": _A_in["w_uk"],
        "A_w_uv": _A_in["w_uv"],
        "A_w_o": _A_in["w_o"],
        "B_x": _B_in["x"],
        "B_w1": _B_in["w1"],
        "B_w2": _B_in["w2"],
        "gate_w": _w((lambda *s: torch.randn(*s, dtype=torch.bfloat16) * 0.05)(640) * 16.0),
    }

def reference(A_x, A_c_kv, A_w_q, A_w_uk, A_w_uv, A_w_o, B_x, B_w1, B_w2, gate_w):
    def _A_ref(x, c_kv, w_q, w_uk, w_uv, w_o):
        B, Sq, M = x.shape[0], x.shape[1], x.shape[2]
        Sk = c_kv.shape[1]
        H, D = w_q.shape[1], w_q.shape[2]
        q = torch.einsum("bqm,mhd->bhqd", x, w_q)
        k = torch.einsum("bkc,chd->bhkd", c_kv, w_uk)
        v = torch.einsum("bkc,chd->bhkd", c_kv, w_uv)
        scores = torch.einsum("bhqd,bhkd->bhqk", q, k) * (D ** -0.5)
        off = Sk - Sq
        qi = torch.arange(Sq)[:, None]
        kj = torch.arange(Sk)[None, :]
        cmask = kj <= (qi + off)
        scores = torch.where(cmask[None, None], scores, -1e9)
        p = _softmax(scores, axis=-1)
        ctx = torch.einsum("bhqk,bhkd->bhqd", p, v)
        return torch.einsum("bhqd,hdm->bqm", ctx, w_o)

    def _B_ref(x, w1, w2):
        h = torch.einsum("bsd,df->bsf", x, w1)
        h = _silu(h)
        out = torch.einsum("bsf,fd->bsd", h, w2)
        return out

    x = A_x
    g = _sigmoid((x * gate_w).sum(-1, keepdims=True))
    a = _A_ref(x, A_c_kv, A_w_q, A_w_uk, A_w_uv, A_w_o)
    b = _B_ref(x, B_w1, B_w2)
    return g * a + (1 - g) * b
```

```cpp
#include <cuda_runtime.h>
#include <cuda.h>
#include <cuda_bf16.h>
#include <stdint.h>

namespace {

constexpr int NCTA = 128;
constexpr int NTHREADS = 320;
constexpr unsigned SENT = 0xFFFFFFFFu;
constexpr int SPIN_MAX = 1 << 18;

constexpr int SM_WUK = 0;
constexpr int SM_CKV = SM_WUK + 32768;
constexpr int SM_WUV = SM_CKV + 65536;
constexpr int SM_W1  = SM_WUV + 32768;
constexpr int SM_W2  = SM_W1 + 20480;
constexpr int SM_WO  = SM_W2 + 20480;
constexpr int SM_TILES_END = SM_WO + 40960;
constexpr int SM_RED  = SM_TILES_END;
constexpr int SM_ML   = SM_RED + 4096;
constexpr int SM_P    = SM_ML + 64;
constexpr int SM_VF   = SM_P + 2304;
constexpr int SM_XS   = SM_VF + 640;
constexpr int SM_CF   = SM_XS + 1280;
constexpr int SM_G    = SM_CF + 96;
constexpr int SM_BAR  = SM_G + 32;
constexpr int SM_END  = SM_BAR + 32 * 8;
constexpr int SM_SP   = SM_WUK;
static_assert(SM_BAR % 8 == 0, "");
constexpr int SMEM_BYTES = SM_END + 1024;

constexpr int NCHUNK = 20;

struct Params {
    CUtensorMap m[6];
    const __nv_bfloat16* x;
    const __nv_bfloat16* wq;
    const __nv_bfloat16* gate;
    __nv_bfloat16* out;
};

__device__ __align__(128) unsigned g_e1[NCTA * 128];
__device__ __align__(128) unsigned g_e2[32 * 256];
__device__ __align__(128) uint4    g_e3[32 * 64 * 64];
__device__ __align__(128) uint4    g_st[32 * 64 * 2];
__device__ __align__(128) unsigned g_e35[NCTA * 192];
__device__ __align__(128) uint4    g_e4[80 * NCTA * 2];

#define STAMP(i)
#define STAMP_T(t, i)

__device__ __forceinline__ unsigned clock32() { unsigned c; asm volatile("mov.u32 %0, %%clock;" : "=r"(c) :: "memory"); return c; }
__device__ __forceinline__ unsigned gtimer() { unsigned c; asm volatile("mov.u32 %0, %%globaltimer_lo;" : "=r"(c) :: "memory"); return c; }

__device__ __forceinline__ uint4 ldg_stream(const void* p) {
    uint4 v;
    asm volatile("ld.global.nc.L1::no_allocate.v4.u32 {%0,%1,%2,%3}, [%4];"
                 : "=r"(v.x), "=r"(v.y), "=r"(v.z), "=r"(v.w) : "l"(p));
    return v;
}
__device__ __forceinline__ uint4 ld_poll4(const void* p) {
    uint4 v;
    asm volatile("ld.relaxed.gpu.global.v4.u32 {%0,%1,%2,%3}, [%4];"
                 : "=r"(v.x), "=r"(v.y), "=r"(v.z), "=r"(v.w) : "l"(p) : "memory");
    return v;
}
__device__ __forceinline__ uint2 ld_poll2(const void* p) {
    uint2 v;
    asm volatile("ld.relaxed.gpu.global.v2.u32 {%0,%1}, [%2];" : "=r"(v.x), "=r"(v.y) : "l"(p) : "memory");
    return v;
}
__device__ __forceinline__ unsigned ld_poll1(const void* p) {
    unsigned v;
    asm volatile("ld.relaxed.gpu.global.u32 %0, [%1];" : "=r"(v) : "l"(p) : "memory");
    return v;
}
__device__ __forceinline__ void st_pub4(void* p, unsigned a, unsigned b, unsigned c, unsigned d) {
    asm volatile("st.relaxed.gpu.global.v4.u32 [%0], {%1,%2,%3,%4};" :: "l"(p), "r"(a), "r"(b), "r"(c), "r"(d) : "memory");
}
__device__ __forceinline__ void st_pub2(void* p, unsigned a, unsigned b) {
    asm volatile("st.relaxed.gpu.global.v2.u32 [%0], {%1,%2};" :: "l"(p), "r"(a), "r"(b) : "memory");
}
__device__ __forceinline__ void st_pub1(void* p, unsigned a) {
    asm volatile("st.relaxed.gpu.global.u32 [%0], %1;" :: "l"(p), "r"(a) : "memory");
}
__device__ __forceinline__ unsigned nz(float v) { unsigned u = __float_as_uint(v); return u ? u : 0x80000000u; }
__device__ __forceinline__ bool has(const uint4& v, unsigned s) { return (v.x == s) | (v.y == s) | (v.z == s) | (v.w == s); }

__device__ __forceinline__ void mbar_wait(uint32_t bar) {
    uint32_t ok;
    int it = 0;
    do {
        asm volatile("{.reg .pred p; mbarrier.try_wait.parity.shared::cta.b64 p, [%1], 0; selp.u32 %0,1,0,p;}"
                     : "=r"(ok) : "r"(bar) : "memory");
    } while (!ok && ++it < SPIN_MAX);
}
__device__ __forceinline__ void bar_sync(int id, int n) { asm volatile("bar.sync %0, %1;" :: "r"(id), "r"(n) : "memory"); }
__device__ __forceinline__ void bar_arrive(int id, int n) { asm volatile("bar.arrive %0, %1;" :: "r"(id), "r"(n) : "memory"); }

__device__ __forceinline__ void ldsm4(uint32_t a, uint32_t (&r)[4]) {
    asm volatile("ldmatrix.sync.aligned.m8n8.x4.shared.b16 {%0,%1,%2,%3}, [%4];"
                 : "=r"(r[0]), "=r"(r[1]), "=r"(r[2]), "=r"(r[3]) : "r"(a) : "memory");
}
__device__ __forceinline__ void ldsm4t(uint32_t a, uint32_t (&r)[4]) {
    asm volatile("ldmatrix.sync.aligned.m8n8.x4.trans.shared.b16 {%0,%1,%2,%3}, [%4];"
                 : "=r"(r[0]), "=r"(r[1]), "=r"(r[2]), "=r"(r[3]) : "r"(a) : "memory");
}
__device__ __forceinline__ void mma(float (&c)[4], uint32_t a0, uint32_t a1, uint32_t a2, uint32_t a3, uint32_t b0, uint32_t b1) {
    asm volatile("mma.sync.aligned.m16n8k16.row.col.f32.bf16.bf16.f32 {%0,%1,%2,%3}, {%4,%5,%6,%7}, {%8,%9}, {%0,%1,%2,%3};"
                 : "+f"(c[0]), "+f"(c[1]), "+f"(c[2]), "+f"(c[3])
                 : "r"(a0), "r"(a1), "r"(a2), "r"(a3), "r"(b0), "r"(b1));
}
__device__ __forceinline__ uint32_t pack_bf16(float lo, float hi) {
    uint32_t r;
    asm("cvt.rn.bf16x2.f32 %0, %1, %2;" : "=r"(r) : "f"(hi), "f"(lo));
    return r;
}
__device__ __forceinline__ float bf_lo(uint32_t w) { return __uint_as_float(w << 16); }
__device__ __forceinline__ float bf_hi(uint32_t w) { return __uint_as_float(w & 0xFFFF0000u); }
__device__ __forceinline__ float ex2(float x) { float y; asm("ex2.approx.ftz.f32 %0, %1;" : "=f"(y) : "f"(x)); return y; }
__device__ __forceinline__ uint4 lds128(uint32_t a) {
    uint4 v;
    asm volatile("ld.shared.v4.u32 {%0,%1,%2,%3}, [%4];" : "=r"(v.x), "=r"(v.y), "=r"(v.z), "=r"(v.w) : "r"(a) : "memory");
    return v;
}
__device__ __forceinline__ uint32_t lds32(uint32_t a) {
    uint32_t v;
    asm volatile("ld.shared.u32 %0, [%1];" : "=r"(v) : "r"(a) : "memory");
    return v;
}
__device__ __forceinline__ void sts128(uint32_t a, float x, float y, float z, float w) {
    asm volatile("st.shared.v4.f32 [%0], {%1,%2,%3,%4};" :: "r"(a), "f"(x), "f"(y), "f"(z), "f"(w) : "memory");
}
__device__ __forceinline__ void sts64(uint32_t a, uint32_t x, uint32_t y) {
    asm volatile("st.shared.v2.u32 [%0], {%1,%2};" :: "r"(a), "r"(x), "r"(y) : "memory");
}
__device__ __forceinline__ void sts16(uint32_t a, uint32_t x) {
    asm volatile("st.shared.u16 [%0], %1;" :: "r"(a), "h"((unsigned short)x) : "memory");
}
__device__ __forceinline__ void fma8(float (&acc)[8], float s, const uint4& v) {
    acc[0] = fmaf(s, bf_lo(v.x), acc[0]); acc[1] = fmaf(s, bf_hi(v.x), acc[1]);
    acc[2] = fmaf(s, bf_lo(v.y), acc[2]); acc[3] = fmaf(s, bf_hi(v.y), acc[3]);
    acc[4] = fmaf(s, bf_lo(v.z), acc[4]); acc[5] = fmaf(s, bf_hi(v.z), acc[5]);
    acc[6] = fmaf(s, bf_lo(v.w), acc[6]); acc[7] = fmaf(s, bf_hi(v.w), acc[7]);
}

#define T0_NS 1000
#define DT_NS 328

__global__ void __launch_bounds__(NTHREADS, 1)
fused_kernel(const __grid_constant__ Params P)
{
    extern __shared__ unsigned char smem_raw[];
    const int tid = threadIdx.x;
    const int b = (blockIdx.x & 1) * 64 + (blockIdx.x >> 1);
    const int h = b >> 2, j = b & 3;
    const int ks = b & 63, hh = b >> 6;
    const int warp = tid >> 5, lane = tid & 31;
    const uint32_t sm = ((uint32_t)__cvta_generic_to_shared(smem_raw) + 1023u) & ~1023u;
    const bool ffn = h < 27;

    if (warp < 8) {
        const int g = lane >> 2, t = lane & 3;
        const int r16 = tid >> 4, c16 = tid & 15;
        {
            const int m0 = 160 * j + 10 * r16;
            const __nv_bfloat16* wp = P.wq + (size_t)m0 * 4096 + h * 128 + c16 * 8;
            uint4 v[10];
#pragma unroll
            for (int i = 0; i < 10; i++) v[i] = ldg_stream(wp + i * 4096);
            uint32_t xw[5];
#pragma unroll
            for (int i = 0; i < 5; i++) xw[i] = __ldg(reinterpret_cast<const uint32_t*>(P.x + m0) + i);
            if (tid < 128) st_pub1(&g_e1[b * 128 + tid], 0u);
            if (t == 0) st_pub1(&g_e2[h * 256 + (4 * j + (warp >> 1)) * 16 + (g & 3) * 4 + 2 * (warp & 1) + (g >> 2)], 0u);
            float acc[8];
#pragma unroll
            for (int e = 0; e < 8; e++) acc[e] = 0.f;
#pragma unroll
            for (int i = 0; i < 10; i++) fma8(acc, (i & 1) ? bf_hi(xw[i >> 1]) : bf_lo(xw[i >> 1]), v[i]);
#pragma unroll
            for (int e = 0; e < 8; e++) acc[e] += __shfl_xor_sync(0xffffffffu, acc[e], 16);
            if (lane < 16) {
                sts128(sm + SM_RED + warp * 512 + c16 * 32, acc[0], acc[1], acc[2], acc[3]);
                sts128(sm + SM_RED + warp * 512 + c16 * 32 + 16, acc[4], acc[5], acc[6], acc[7]);
            }
        }
        STAMP(0);
        bar_sync(1, 288);
        if (tid < 128) {
            float s = 0.f;
#pragma unroll
            for (int w = 0; w < 8; w++) s += __uint_as_float(lds32(sm + SM_RED + w * 512 + tid * 4));
            unsigned u = __float_as_uint(s);
            st_pub1(&g_e1[b * 128 + tid], u ? u : 0x80000000u);
            unsigned p[4];
            int it = 0;
            do {
#pragma unroll
                for (int s4 = 0; s4 < 4; s4++) p[s4] = ld_poll1(&g_e1[(4 * h + s4) * 128 + tid]);
            } while (((p[0] == 0) | (p[1] == 0) | (p[2] == 0) | (p[3] == 0)) && ++it < SPIN_MAX);
            float q = (__uint_as_float(p[0]) + __uint_as_float(p[1])) + (__uint_as_float(p[2]) + __uint_as_float(p[3]));
            sts16(sm + SM_VF + ((tid >> 1) & 3) * 80 + (tid >> 4) * 8 + ((tid >> 3) & 1) * 4 + (tid & 1) * 2, pack_bf16(q, 0.f));
        }
        STAMP(1);
        bar_sync(2, 288);
        {
            uint4 qf[4];
#pragma unroll
            for (int i = 0; i < 4; i++) qf[i] = lds128(sm + SM_VF + t * 80 + i * 16);
            mbar_wait(sm + SM_BAR + 8 * (warp >> 1));
            const int row = (warp & 1) * 16 + 2 * (lane & 7) + ((lane >> 3) & 1);
            const uint32_t base = sm + SM_WUK + (warp >> 1) * 8192 + row * 128;
            float c0[4] = {0.f, 0.f, 0.f, 0.f}, c1[4] = {0.f, 0.f, 0.f, 0.f};
#pragma unroll
            for (int i = 0; i < 4; i++) {
                uint32_t a[4];
                ldsm4(base + (i >> 1) * 4096 + ((((i & 1) * 4 + (lane >> 4)) ^ (row & 7)) << 4), a);
                mma(c0, a[0], a[1], a[2], a[3], qf[i].x, qf[i].y);
                ldsm4(base + (i >> 1) * 4096 + ((((i & 1) * 4 + 2 + (lane >> 4)) ^ (row & 7)) << 4), a);
                mma(c1, a[0], a[1], a[2], a[3], qf[i].z, qf[i].w);
            }
            const float sc = 0.08838834764831845f * 1.4426950408889634f;
            uint32_t u = pack_bf16((c0[0] + c1[0]) * sc, (c0[2] + c1[2]) * sc);
            if (t == 0)
                st_pub1(&g_e2[h * 256 + (4 * j + (warp >> 1)) * 16 + (g & 3) * 4 + 2 * (warp & 1) + (g >> 2)], u ? u : 0x80000000u);
        }
        STAMP(2);
        {
            uint4 qa[4];
            {
                const unsigned* qp = &g_e2[(16 * hh + g) * 256 + warp * 32 + t * 4];
                int it = 0;
                bool bad0 = true, bad1 = true;
                do {
                    if (bad0) { qa[0] = ld_poll4(qp); qa[1] = ld_poll4(qp + 16); }
                    if (bad1) { qa[2] = ld_poll4(qp + 8 * 256); qa[3] = ld_poll4(qp + 8 * 256 + 16); }
                    bad0 = has(qa[0], 0u) | has(qa[1], 0u);
                    bad1 = has(qa[2], 0u) | has(qa[3], 0u);
                } while ((bad0 | bad1) && ++it < SPIN_MAX);
            }
            __syncwarp();
            STAMP(3);
            mbar_wait(sm + SM_BAR + 8 * (4 + (warp >> 1)));
            STAMP(4);
            const uint32_t cbase = sm + SM_CKV + warp * 8192;
            {
                const uint32_t a0 = cbase + (lane & 7) * 128 + (((lane >> 3) ^ (lane & 7)) << 4);
                float s[8][4];
#pragma unroll
                for (int n = 0; n < 8; n++) {
                    uint32_t bf[4];
                    s[n][0] = s[n][1] = s[n][2] = s[n][3] = 0.f;
                    ldsm4(a0 + n * 1024, bf);
                    mma(s[n], qa[0].x, qa[2].x, qa[0].y, qa[2].y, bf[0], bf[1]);
                    mma(s[n], qa[0].z, qa[2].z, qa[0].w, qa[2].w, bf[2], bf[3]);
                    ldsm4((a0 + n * 1024) ^ 64, bf);
                    mma(s[n], qa[1].x, qa[3].x, qa[1].y, qa[3].y, bf[0], bf[1]);
                    mma(s[n], qa[1].z, qa[3].z, qa[1].w, qa[3].w, bf[2], bf[3]);
                }
                __syncwarp();
            #pragma unroll
                for (int n = 0; n < 8; n++) {
                    const uint32_t o = sm + SM_SP + (warp >> 1) * 8192 + (warp & 1) * 2048 + g * 256 + ((n ^ (g & 3)) << 5) + t * 8;
                    sts64(o, __float_as_uint(s[n][0]), __float_as_uint(s[n][1]));
                    sts64(o + 4096, __float_as_uint(s[n][2]), __float_as_uint(s[n][3]));
                }
            }
            uint32_t ct[8][2][4];
#pragma unroll
            for (int n = 0; n < 8; n++) {
                const uint32_t a = cbase + lane * 128 + ((n ^ (lane & 7)) << 4);
                ldsm4t(a, ct[n][0]);
                ldsm4t(a + 4096, ct[n][1]);
            }
            bar_sync(3, 256);
            {
                const int hl = 2 * warp + (lane >> 4);
                const int k4 = lane & 15;
                const uint32_t o = sm + SM_SP + (hl >> 3) * 4096 + (hl & 7) * 256 + (((k4 >> 1) ^ (hl & 3)) << 5) + (k4 & 1) * 16;
                float s0 = 0.f, s1 = 0.f, s2 = 0.f, s3 = 0.f;
#pragma unroll
                for (int w = 0; w < 8; w++) {
                    uint4 v = lds128(o + (w >> 1) * 8192 + (w & 1) * 2048);
                    s0 += __uint_as_float(v.x); s1 += __uint_as_float(v.y);
                    s2 += __uint_as_float(v.z); s3 += __uint_as_float(v.w);
                }
                float m = fmaxf(fmaxf(s0, s1), fmaxf(s2, s3));
#pragma unroll
                for (int d = 1; d < 16; d <<= 1) m = fmaxf(m, __shfl_xor_sync(0xffffffffu, m, d));
                const uint32_t p01 = pack_bf16(ex2(s0 - m), ex2(s1 - m));
                const uint32_t p23 = pack_bf16(ex2(s2 - m), ex2(s3 - m));
                sts64(sm + SM_P + hl * 144 + k4 * 8, p01, p23);
                float l = (bf_lo(p01) + bf_hi(p01)) + (bf_lo(p23) + bf_hi(p23));
#pragma unroll
                for (int d = 1; d < 16; d <<= 1) l += __shfl_xor_sync(0xffffffffu, l, d);
                if (k4 == 0) st_pub2(&g_st[((16 * hh + hl) * 64 + ks) * 2], __float_as_uint(m + 0.f), __float_as_uint(l));
            }
            bar_sync(3, 256);
            {
                float o[8][4];
#pragma unroll
                for (int n = 0; n < 8; n++) o[n][0] = o[n][1] = o[n][2] = o[n][3] = 0.f;
                const uint32_t pa = sm + SM_P + ((lane & 7) + ((lane >> 3) & 1) * 8) * 144 + (lane >> 4) * 16;
#pragma unroll
                for (int s = 0; s < 4; s++) {
                    uint32_t a[4];
                    ldsm4(pa + s * 32, a);
#pragma unroll
                    for (int n = 0; n < 8; n++)
                        mma(o[n], a[0], a[1], a[2], a[3], ct[n][s >> 1][(s & 1) * 2], ct[n][s >> 1][(s & 1) * 2 + 1]);
                }
                uint4* op = &g_e3[((16 * hh + g) * 64 + ks) * 64 + warp * 8 + t];
#pragma unroll
                for (int q = 0; q < 2; q++) {
                    st_pub4(op + q * 4, pack_bf16(o[4 * q][0], o[4 * q][1]), pack_bf16(o[4 * q + 1][0], o[4 * q + 1][1]),
                            pack_bf16(o[4 * q + 2][0], o[4 * q + 2][1]), pack_bf16(o[4 * q + 3][0], o[4 * q + 3][1]));
                    st_pub4(op + 8 * 64 * 64 + q * 4, pack_bf16(o[4 * q][2], o[4 * q][3]), pack_bf16(o[4 * q + 1][2], o[4 * q + 1][3]),
                            pack_bf16(o[4 * q + 2][2], o[4 * q + 2][3]), pack_bf16(o[4 * q + 3][2], o[4 * q + 3][3]));
                }
            }
        }
        STAMP(5);
        {
            uint4 v[4];
            uint2 st[4];
            const uint4* dp = &g_e3[(h * 64 + 4 * r16) * 64 + 16 * j + c16];
            const uint4* sp = &g_st[(h * 64 + 4 * r16) * 2];
            bool bad[4] = {true, true, true, true};
            int it = 0;
            bool any;
            do {
#pragma unroll
                for (int i = 0; i < 4; i++)
                    if (bad[i]) { v[i] = ld_poll4(dp + i * 64); st[i] = ld_poll2(sp + i * 2); }
                any = false;
#pragma unroll
                for (int i = 0; i < 4; i++) { bad[i] = has(v[i], SENT) | (st[i].x == SENT) | (st[i].y == SENT); any |= bad[i]; }
            } while (any && ++it < SPIN_MAX);
            __syncwarp();
            STAMP(6);
            float m = fmaxf(fmaxf(__uint_as_float(st[0].x), __uint_as_float(st[1].x)), fmaxf(__uint_as_float(st[2].x), __uint_as_float(st[3].x)));
            m = fmaxf(m, __shfl_xor_sync(0xffffffffu, m, 16));
            float acc[8], l = 0.f;
#pragma unroll
            for (int e = 0; e < 8; e++) acc[e] = 0.f;
#pragma unroll
            for (int i = 0; i < 4; i++) {
                const float f = ex2(__uint_as_float(st[i].x) - m);
                l = fmaf(f, __uint_as_float(st[i].y), l);
                fma8(acc, f, v[i]);
            }
            l += __shfl_xor_sync(0xffffffffu, l, 16);
#pragma unroll
            for (int e = 0; e < 8; e++) acc[e] += __shfl_xor_sync(0xffffffffu, acc[e], 16);
            if (lane < 16) {
                sts128(sm + SM_RED + warp * 512 + c16 * 32, acc[0], acc[1], acc[2], acc[3]);
                sts128(sm + SM_RED + warp * 512 + c16 * 32 + 16, acc[4], acc[5], acc[6], acc[7]);
                if (lane == 0) sts64(sm + SM_ML + warp * 8, __float_as_uint(m), __float_as_uint(l));
            }
        }
        bar_sync(3, 256);
        if (t == 0) st_pub1(&g_e2[h * 256 + (4 * j + (warp >> 1)) * 16 + (g & 3) * 4 + 2 * (warp & 1) + (g >> 2)], 0u);
        if (tid < 128) {
            st_pub1(&g_e1[b * 128 + tid], 0u);
            uint4 ml[4];
#pragma unroll
            for (int i = 0; i < 4; i++) ml[i] = lds128(sm + SM_ML + i * 16);
            float M = __uint_as_float(ml[0].x);
#pragma unroll
            for (int i = 0; i < 4; i++) M = fmaxf(M, fmaxf(__uint_as_float(ml[i].x), __uint_as_float(ml[i].z)));
            float L = 0.f, s = 0.f;
#pragma unroll
            for (int i = 0; i < 4; i++) {
                const float f0 = ex2(__uint_as_float(ml[i].x) - M), f1 = ex2(__uint_as_float(ml[i].z) - M);
                L = fmaf(f0, __uint_as_float(ml[i].y), L);
                L = fmaf(f1, __uint_as_float(ml[i].w), L);
                s = fmaf(f0, __uint_as_float(lds32(sm + SM_RED + (2 * i) * 512 + tid * 4)), s);
                s = fmaf(f1, __uint_as_float(lds32(sm + SM_RED + (2 * i + 1) * 512 + tid * 4)), s);
            }
            s = __fdividef(s, L);
            const uint32_t hi = pack_bf16(s, 0.f);
            const uint32_t lo = pack_bf16(s - bf_lo(hi), 0.f);
            const uint32_t o = sm + SM_VF + ((tid >> 3) & 3) * 80 + (tid >> 5) * 16 + (tid & 7) * 2;
            sts16(o, hi);
            sts16(o + 320, lo);
        }
        bar_sync(3, 256);
        STAMP(7);
        {
            float c[2][4] = {{0.f, 0.f, 0.f, 0.f}, {0.f, 0.f, 0.f, 0.f}};
            const uint32_t base = sm + SM_WUV + (warp >> 2) * 4096 + lane * 128;
#pragma unroll
            for (int i = 0; i < 4; i++) {
                const uint4 hi = lds128(sm + SM_VF + t * 80 + i * 16);
                const uint4 lo = lds128(sm + SM_VF + 320 + t * 80 + i * 16);
                mbar_wait(sm + SM_BAR + 8 * (8 + i));
#pragma unroll
                for (int n = 0; n < 2; n++) {
                    uint32_t bf[4];
                    ldsm4t(base + i * 8192 + (((2 * (warp & 3) + n) ^ (lane & 7)) << 4), bf);
                    mma(c[n], hi.x, lo.x, hi.y, lo.y, bf[0], bf[1]);
                    mma(c[n], hi.z, lo.z, hi.w, lo.w, bf[2], bf[3]);
                }
            }
            if (g == 0) {
#pragma unroll
                for (int n = 0; n < 2; n++)
                    st_pub2(&g_e35[b * 192 + 16 * warp + 8 * n + 2 * t], __float_as_uint(c[n][0] + c[n][2]), __float_as_uint(c[n][1] + c[n][3]));
            }
        }
        STAMP(8);
        if (ffn) {
            float c[4] = {0.f, 0.f, 0.f, 0.f};
            const uint32_t base = sm + SM_W1 + lane * 128 + ((warp ^ (lane & 7)) << 4);
            const uint32_t xa = sm + SM_XS + 320 * j + 4 * t;
            mbar_wait(sm + SM_BAR + 8 * 12);
            mbar_wait(sm + SM_BAR + 8 * 13);
#pragma unroll
            for (int i = 0; i < 5; i++) {
                uint32_t bf[4];
                ldsm4t(base + i * 4096, bf);
                mma(c, lds32(xa + i * 64), 0u, lds32(xa + i * 64 + 16), 0u, bf[0], bf[1]);
                mma(c, lds32(xa + i * 64 + 32), 0u, lds32(xa + i * 64 + 48), 0u, bf[2], bf[3]);
            }
            if (g == 0) st_pub2(&g_e35[b * 192 + 128 + 8 * warp + 2 * t], __float_as_uint(c[0]), __float_as_uint(c[1]));
        }
        STAMP(9);
        if (tid < 48) {
            float v = 0.f;
            if (tid < 32 || ffn) {
                const unsigned* p = &g_e35[4 * h * 192 + (tid < 32 ? 32 * j + tid : 96 + 16 * j + tid)];
                unsigned u[4];
                int it = 0;
                do {
#pragma unroll
                    for (int s4 = 0; s4 < 4; s4++) u[s4] = ld_poll1(p + s4 * 192);
                } while (((u[0] == SENT) | (u[1] == SENT) | (u[2] == SENT) | (u[3] == SENT)) && ++it < SPIN_MAX);
                v = (__uint_as_float(u[0]) + __uint_as_float(u[1])) + (__uint_as_float(u[2]) + __uint_as_float(u[3]));
                if (tid >= 32) {
                    v = bf_lo(pack_bf16(v, 0.f));
                    v = __fdividef(v, 1.f + __expf(-v));
                }
            }
            sts16(sm + SM_CF + tid * 2, pack_bf16(v, 0.f));
        }
        bar_sync(3, 256);
        bar_arrive(4, 288);
        STAMP(10);
        {
            float c[10][4];
#pragma unroll
            for (int n = 0; n < 10; n++) c[n][0] = c[n][1] = c[n][2] = c[n][3] = 0.f;
            const int half = warp >> 2;
            uint32_t off[5];
#pragma unroll
            for (int i = 0; i < 5; i++) {
                const int N = 10 * (warp & 3) + 2 * i + (lane >> 4);
                off[i] = (N >> 3) * 2048 + (lane & 15) * 128 + (((N & 7) ^ (lane & 7)) << 4);
            }
            if (ffn) {
                const uint32_t a1 = lds32(sm + SM_CF + 64 + 4 * t), a3 = lds32(sm + SM_CF + 80 + 4 * t);
                mbar_wait(sm + SM_BAR + 8 * (14 + half));
#pragma unroll
                for (int i = 0; i < 5; i++) {
                    uint32_t bf[4];
                    ldsm4t(sm + SM_W2 + half * 10240 + off[i], bf);
                    mma(c[2 * i], 0u, a1, 0u, a3, bf[0], bf[1]);
                    mma(c[2 * i + 1], 0u, a1, 0u, a3, bf[2], bf[3]);
                }
            }
#pragma unroll
            for (int s = 0; s < 2; s++) {
                const uint32_t a0 = lds32(sm + SM_CF + s * 32 + 4 * t), a2 = lds32(sm + SM_CF + s * 32 + 16 + 4 * t);
                mbar_wait(sm + SM_BAR + 8 * (16 + 2 * s + half));
#pragma unroll
                for (int i = 0; i < 5; i++) {
                    uint32_t bf[4];
                    ldsm4t(sm + SM_WO + (2 * s + half) * 10240 + off[i], bf);
                    mma(c[2 * i], a0, 0u, a2, 0u, bf[0], bf[1]);
                    mma(c[2 * i + 1], a0, 0u, a2, 0u, bf[2], bf[3]);
                }
            }
            STAMP(11);
            const float gt = __uint_as_float(lds32(sm + SM_G));
            if (g == 0) {
                unsigned* op = reinterpret_cast<unsigned*>(g_e4) + ((10 * warp) * NCTA + b) * 8 + 2 * t;
#pragma unroll
                for (int n = 0; n < 10; n++)
                    st_pub2(op + n * NCTA * 8, nz(gt * c[n][0] + (1.f - gt) * c[n][2]), nz(gt * c[n][1] + (1.f - gt) * c[n][3]));
            }
        }
        STAMP(12);
    } else if (warp == 8) {
        const unsigned t0 = gtimer();
        const uint32_t bar = sm + SM_BAR + 8 * lane;
        asm volatile("mbarrier.init.shared::cta.b64 [%0], 1;" :: "r"(bar) : "memory");
        asm volatile("fence.mbarrier_init.release.cluster;" ::: "memory");
        bar_arrive(1, 288);
        if (lane < 6) asm volatile("prefetch.tensormap [%0];" :: "l"(&P.m[lane]) : "memory");
        int map, c1, c2;
        uint32_t dst, bytes, due;
        const int k = lane;
        if (k < 4)       { map = 0; c1 = 128 * j + 32 * k;        c2 = 2 * h;        dst = SM_WUK + k * 8192;         bytes = 8192;  due = k * DT_NS; }
        else if (k < 8)  { map = 1; c1 = 64 * ks;                 c2 = 2 * (k - 4);  dst = SM_CKV + (k - 4) * 16384;  bytes = 16384; due = k * DT_NS; }
        else if (k < 12) { map = 2; c1 = 128 * j + 32 * (k - 8);  c2 = 2 * h;        dst = SM_WUV + (k - 8) * 8192;   bytes = 8192;  due = k * DT_NS; }
        else if (k < 14) { map = 3; c1 = 160 * j + 80 * (k - 12); c2 = h;            dst = SM_W1 + (k - 12) * 10240;  bytes = ffn ? 10240 : 0; due = 12 * DT_NS + (k - 12) * (DT_NS * 135 / 128); }
        else if (k < 16) { map = 4; c1 = 16 * b;                  c2 = 5 * (k - 14); dst = SM_W2 + (k - 14) * 10240;  bytes = ffn ? 10240 : 0; due = 12 * DT_NS + (k - 12) * (DT_NS * 135 / 128); }
        else             { map = 5; c1 = 32 * b + 16 * ((k - 16) >> 1); c2 = 5 * (k & 1); dst = SM_WO + (k - 16) * 10240; bytes = k < NCHUNK ? 10240 : 0;
                           due = 12 * DT_NS + 4 * (DT_NS * 135 / 128) + (k - 16) * (DT_NS * 5 / 4); }
        due += T0_NS;
        bool pending = bytes != 0;
        while (__any_sync(0xffffffffu, pending)) {
            const unsigned now = gtimer() - t0;
            if (pending && now >= due) {
                asm volatile("mbarrier.arrive.expect_tx.shared::cta.b64 _, [%0], %1;" :: "r"(bar), "r"(bytes) : "memory");
                asm volatile("cp.async.bulk.tensor.3d.shared::cluster.global.mbarrier::complete_tx::bytes [%0], [%1, {%3,%4,%5}], [%2];"
                             :: "r"(sm + dst), "l"(&P.m[map]), "r"(bar), "r"(0), "r"(c1), "r"(c2) : "memory");
                pending = false;
            }
        }
    } else {
        uint32_t xw[10], gw[10];
#pragma unroll
        for (int i = 0; i < 10; i++) {
            xw[i] = __ldg(reinterpret_cast<const uint32_t*>(P.x) + i * 32 + lane);
            gw[i] = __ldg(reinterpret_cast<const uint32_t*>(P.gate) + i * 32 + lane);
        }
        {
            uint4* p3 = &g_e3[(16 * hh * 64 + ks) * 64 + lane];
#pragma unroll 4
            for (int i = 0; i < 16; i++) {
                st_pub4(p3 + i * 64 * 64, SENT, SENT, SENT, SENT);
                st_pub4(p3 + i * 64 * 64 + 32, SENT, SENT, SENT, SENT);
            }
            st_pub4(&g_st[((16 * hh + (lane >> 1)) * 64 + ks) * 2 + (lane & 1)], SENT, SENT, SENT, SENT);
            st_pub4(&g_e35[b * 192 + lane * 4], SENT, SENT, SENT, SENT);
            if (lane < 16) st_pub4(&g_e35[b * 192 + 128 + lane * 4], SENT, SENT, SENT, SENT);
#pragma unroll
            for (int i = 0; i < 5; i++) st_pub4(&g_e4[((i * 16 + (lane >> 1)) * NCTA + b) * 2 + (lane & 1)], 0u, 0u, 0u, 0u);
        }
        float z = 0.f;
#pragma unroll
        for (int i = 0; i < 10; i++) {
            asm volatile("st.shared.u32 [%0], %1;" :: "r"(sm + SM_XS + (i * 32 + lane) * 4), "r"(xw[i]) : "memory");
            z = fmaf(bf_lo(xw[i]), bf_lo(gw[i]), z);
            z = fmaf(bf_hi(xw[i]), bf_hi(gw[i]), z);
        }
#pragma unroll
        for (int d = 1; d < 32; d <<= 1) z += __shfl_xor_sync(0xffffffffu, z, d);
        if (lane == 0) asm volatile("st.shared.f32 [%0], %1;" :: "r"(sm + SM_G), "f"(1.f / (1.f + __expf(-z))) : "memory");
        __threadfence();
        STAMP_T(288, 13);
        bar_arrive(2, 288);
        bar_sync(4, 288);
        if (b < 80) {
            const uint4* p = &g_e4[b * NCTA * 2 + lane];
            uint4 v[8];
            bool bad[8];
#pragma unroll
            for (int i = 0; i < 8; i++) bad[i] = true;
            int it = 0;
            bool any;
            do {
#pragma unroll
                for (int i = 0; i < 8; i++) if (bad[i]) v[i] = ld_poll4(p + i * 32);
                any = false;
#pragma unroll
                for (int i = 0; i < 8; i++) { bad[i] = has(v[i], 0u); any |= bad[i]; }
            } while (any && ++it < SPIN_MAX);
            __syncwarp();
            float s0 = 0.f, s1 = 0.f, s2 = 0.f, s3 = 0.f;
#pragma unroll
            for (int i = 0; i < 8; i++) {
                s0 += __uint_as_float(v[i].x); s1 += __uint_as_float(v[i].y);
                s2 += __uint_as_float(v[i].z); s3 += __uint_as_float(v[i].w);
            }
#pragma unroll
            for (int d = 2; d < 32; d <<= 1) {
                s0 += __shfl_xor_sync(0xffffffffu, s0, d); s1 += __shfl_xor_sync(0xffffffffu, s1, d);
                s2 += __shfl_xor_sync(0xffffffffu, s2, d); s3 += __shfl_xor_sync(0xffffffffu, s3, d);
            }
            if (lane < 2) *reinterpret_cast<uint2*>(P.out + b * 8 + lane * 4) = make_uint2(pack_bf16(s0, s1), pack_bf16(s2, s3));
#pragma unroll
            for (int i = 0; i < 8; i++) st_pub4(const_cast<uint4*>(p) + i * 32, 0u, 0u, 0u, 0u);
            STAMP_T(288, 14);
        }
    }
}

typedef CUresult (*EncodeFn)(CUtensorMap*, CUtensorMapDataType, cuuint32_t, void*, const cuuint64_t*, const cuuint64_t*,
                             const cuuint32_t*, const cuuint32_t*, CUtensorMapInterleave, CUtensorMapSwizzle,
                             CUtensorMapL2promotion, CUtensorMapFloatOOBfill);

void make_map(EncodeFn enc, CUtensorMap* m, const void* base, int rows, int cols, int box_rows, int box_blks) {
    cuuint64_t gd[3] = {64, (cuuint64_t)rows, (cuuint64_t)(cols / 64)};
    cuuint64_t gs[2] = {(cuuint64_t)cols * 2, 128};
    cuuint32_t bd[3] = {64, (cuuint32_t)box_rows, (cuuint32_t)box_blks};
    cuuint32_t es[3] = {1, 1, 1};
    enc(m, CU_TENSOR_MAP_DATA_TYPE_BFLOAT16, 3, const_cast<void*>(base), gd, gs, bd, es, CU_TENSOR_MAP_INTERLEAVE_NONE,
        CU_TENSOR_MAP_SWIZZLE_128B, CU_TENSOR_MAP_L2_PROMOTION_NONE, CU_TENSOR_MAP_FLOAT_OOB_FILL_NONE);
}

}

extern "C" void kernel_launch(void* const* d_in, const int* in_sizes, int n_in, void* d_out, int out_size) {
    (void)in_sizes; (void)n_in; (void)out_size;
    static EncodeFn enc = nullptr;
    if (!enc) {
        void* fn = nullptr;
        cudaDriverEntryPointQueryResult st;
        cudaGetDriverEntryPoint("cuTensorMapEncodeTiled", &fn, cudaEnableDefault, &st);
        enc = (EncodeFn)fn;
        cudaFuncSetAttribute(fused_kernel, cudaFuncAttributeMaxDynamicSharedMemorySize, SMEM_BYTES);
    }
    Params p;
    make_map(enc, &p.m[0], d_in[3], 512, 4096, 32, 2);
    make_map(enc, &p.m[1], d_in[1], 4096, 512, 64, 2);
    make_map(enc, &p.m[2], d_in[4], 512, 4096, 32, 2);
    make_map(enc, &p.m[3], d_in[7], 640, 1728, 80, 1);
    make_map(enc, &p.m[4], d_in[8], 1728, 640, 16, 5);
    make_map(enc, &p.m[5], d_in[5], 4096, 640, 16, 5);
    p.x = (const __nv_bfloat16*)d_in[0];
    p.wq = (const __nv_bfloat16*)d_in[2];
    p.gate = (const __nv_bfloat16*)d_in[9];
    p.out = (__nv_bfloat16*)d_out;
    fused_kernel<<<NCTA, NTHREADS, SMEM_BYTES>>>(p);
}
```

```cpp
#include <cuda_runtime.h>
#include <cuda.h>
#include <cuda_bf16.h>
#include <stdint.h>

namespace {

constexpr int NCTA = 128;
constexpr int NTHREADS = 288;
constexpr int SPIN_MAX = 1 << 18;

constexpr int SM_WUK = 0;
constexpr int SM_CKV = SM_WUK + 32768;
constexpr int SM_WUV = SM_CKV + 65536;
constexpr int SM_W1  = SM_WUV + 32768;
constexpr int SM_W2  = SM_W1 + 20480;
constexpr int SM_WO  = SM_W2 + 20480;
constexpr int SM_SPR = SM_WO + 40960;
constexpr int SM_RED = SM_SPR;
constexpr int SM_VF3 = SM_SPR + 8192;
constexpr int SM_ML  = SM_SPR + 12288;
constexpr int SM_P   = SM_WUK + 4096;
constexpr int SM_VF1 = SM_SPR + 16384;
constexpr int SM_XS  = SM_VF1 + 320;
constexpr int SM_XC  = SM_XS + 640;
constexpr int SM_XH  = SM_XC + 256;
constexpr int SM_G   = SM_XH + 256;
constexpr int SM_BAR = SM_G + 32;
constexpr int SM_END = SM_BAR + 32 * 8;
constexpr int SMEM_BYTES = SM_END + 1024;
static_assert(SMEM_BYTES <= 232448, "smem");

constexpr int B_WUK = 0, B_CKV = 4, B_W1 = 8, B_WUV = 10, B_W2 = 14, B_WO = 16, B_SP = 20, B_P = 21, B_XC = 22, B_XH = 23;

struct Params {
    CUtensorMap m[6];
    const __nv_bfloat16* x;
    const __nv_bfloat16* wq;
    const __nv_bfloat16* gate;
    __nv_bfloat16* out;
};

__device__ unsigned g_epoch;
__device__ __align__(128) unsigned g_e1[NCTA * 128];
__device__ __align__(128) unsigned g_e2[32 * 256];
__device__ __align__(128) uint4    g_e3[32 * 32 * 2 * 32];
__device__ __align__(128) uint2    g_st[32 * 32 * 4];
__device__ __align__(128) uint4    g_e4[80 * NCTA * 2];

#define STAMP(i)
#define STAMP_T(t, i)

__device__ __forceinline__ unsigned clock32() { unsigned c; asm volatile("mov.u32 %0, %%clock;" : "=r"(c) :: "memory"); return c; }
__device__ __forceinline__ unsigned gtimer() { unsigned c; asm volatile("mov.u32 %0, %%globaltimer_lo;" : "=r"(c) :: "memory"); return c; }

__device__ __forceinline__ uint4 ldg_stream(const void* p) {
    uint4 v;
    asm volatile("ld.global.nc.L1::no_allocate.v4.u32 {%0,%1,%2,%3}, [%4];"
                 : "=r"(v.x), "=r"(v.y), "=r"(v.z), "=r"(v.w) : "l"(p));
    return v;
}
__device__ __forceinline__ uint4 ld_poll4(const void* p) {
    uint4 v;
    asm volatile("ld.relaxed.gpu.global.v4.u32 {%0,%1,%2,%3}, [%4];"
                 : "=r"(v.x), "=r"(v.y), "=r"(v.z), "=r"(v.w) : "l"(p) : "memory");
    return v;
}
__device__ __forceinline__ uint4 ld_poll2x64(const void* p) {
    uint4 v;
    asm volatile("{.reg .b64 a, b; ld.relaxed.gpu.global.v2.b64 {a, b}, [%4]; mov.b64 {%0,%1}, a; mov.b64 {%2,%3}, b;}"
                 : "=r"(v.x), "=r"(v.y), "=r"(v.z), "=r"(v.w) : "l"(p) : "memory");
    return v;
}
__device__ __forceinline__ uint2 ld_poll64(const void* p) {
    uint2 v;
    asm volatile("{.reg .b64 a; ld.relaxed.gpu.global.b64 a, [%2]; mov.b64 {%0,%1}, a;}" : "=r"(v.x), "=r"(v.y) : "l"(p) : "memory");
    return v;
}
__device__ __forceinline__ unsigned ld_poll1(const void* p) {
    unsigned v;
    asm volatile("ld.relaxed.gpu.global.u32 %0, [%1];" : "=r"(v) : "l"(p) : "memory");
    return v;
}
__device__ __forceinline__ void st_pub2x64(void* p, unsigned a, unsigned b, unsigned c, unsigned d) {
    asm volatile("{.reg .b64 x, y; mov.b64 x, {%1,%2}; mov.b64 y, {%3,%4}; st.relaxed.gpu.global.v2.b64 [%0], {x, y};}"
                 :: "l"(p), "r"(a), "r"(b), "r"(c), "r"(d) : "memory");
}
__device__ __forceinline__ void st_pub64(void* p, unsigned a, unsigned b) {
    asm volatile("{.reg .b64 x; mov.b64 x, {%1,%2}; st.relaxed.gpu.global.b64 [%0], x;}" :: "l"(p), "r"(a), "r"(b) : "memory");
}
__device__ __forceinline__ void st_pub1(void* p, unsigned a) {
    asm volatile("st.relaxed.gpu.global.u32 [%0], %1;" :: "l"(p), "r"(a) : "memory");
}
__device__ __forceinline__ unsigned tagw(unsigned w, unsigned tag) { return (w & ~1u) | tag; }
__device__ __forceinline__ unsigned tagf(float v, unsigned tag) { return (__float_as_uint(v) & ~1u) | tag; }
__device__ __forceinline__ float untagf(unsigned w) { return __uint_as_float(w & ~1u); }

__device__ __forceinline__ void mbar_wait(uint32_t bar) {
    uint32_t ok;
    int it = 0;
#pragma unroll 1
    do {
        asm volatile("{.reg .pred p; mbarrier.try_wait.parity.shared::cta.b64 p, [%1], 0; selp.u32 %0,1,0,p;}"
                     : "=r"(ok) : "r"(bar) : "memory");
    } while (!ok && ++it < SPIN_MAX);
}
__device__ __forceinline__ void mbar_wait_cluster(uint32_t bar) {
    uint32_t ok;
    int it = 0;
#pragma unroll 1
    do {
        asm volatile("{.reg .pred p; mbarrier.try_wait.parity.acquire.cluster.shared::cta.b64 p, [%1], 0; selp.u32 %0,1,0,p;}"
                     : "=r"(ok) : "r"(bar) : "memory");
    } while (!ok && ++it < SPIN_MAX);
}
__device__ __forceinline__ void bar_sync(int id, int n) { asm volatile("bar.sync %0, %1;" :: "r"(id), "r"(n) : "memory"); }
__device__ __forceinline__ void bar_arrive(int id, int n) { asm volatile("bar.arrive %0, %1;" :: "r"(id), "r"(n) : "memory"); }
__device__ __forceinline__ uint32_t mapa(uint32_t a, uint32_t rank) {
    uint32_t r;
    asm("mapa.shared::cluster.u32 %0, %1, %2;" : "=r"(r) : "r"(a), "r"(rank));
    return r;
}
__device__ __forceinline__ void st_async4(uint32_t a, float x, float y, float z, float w, uint32_t bar) {
    asm volatile("st.async.weak.shared::cluster.mbarrier::complete_tx::bytes.v4.f32 [%0], {%1,%2,%3,%4}, [%5];"
                 :: "r"(a), "f"(x), "f"(y), "f"(z), "f"(w), "r"(bar) : "memory");
}
__device__ __forceinline__ void st_async2(uint32_t a, uint32_t x, uint32_t y, uint32_t bar) {
    asm volatile("st.async.weak.shared::cluster.mbarrier::complete_tx::bytes.v2.b32 [%0], {%1,%2}, [%3];"
                 :: "r"(a), "r"(x), "r"(y), "r"(bar) : "memory");
}

__device__ __forceinline__ void ldsm4(uint32_t a, uint32_t (&r)[4]) {
    asm volatile("ldmatrix.sync.aligned.m8n8.x4.shared.b16 {%0,%1,%2,%3}, [%4];"
                 : "=r"(r[0]), "=r"(r[1]), "=r"(r[2]), "=r"(r[3]) : "r"(a) : "memory");
}
__device__ __forceinline__ void ldsm4t(uint32_t a, uint32_t (&r)[4]) {
    asm volatile("ldmatrix.sync.aligned.m8n8.x4.trans.shared.b16 {%0,%1,%2,%3}, [%4];"
                 : "=r"(r[0]), "=r"(r[1]), "=r"(r[2]), "=r"(r[3]) : "r"(a) : "memory");
}
__device__ __forceinline__ void mma(float (&c)[4], uint32_t a0, uint32_t a1, uint32_t a2, uint32_t a3, uint32_t b0, uint32_t b1) {
    asm("mma.sync.aligned.m16n8k16.row.col.f32.bf16.bf16.f32 {%0,%1,%2,%3}, {%4,%5,%6,%7}, {%8,%9}, {%0,%1,%2,%3};"
        : "+f"(c[0]), "+f"(c[1]), "+f"(c[2]), "+f"(c[3])
        : "r"(a0), "r"(a1), "r"(a2), "r"(a3), "r"(b0), "r"(b1));
}
__device__ __forceinline__ uint32_t pack_bf16(float lo, float hi) {
    uint32_t r;
    asm("cvt.rn.bf16x2.f32 %0, %1, %2;" : "=r"(r) : "f"(hi), "f"(lo));
    return r;
}
__device__ __forceinline__ float bf_lo(uint32_t w) { return __uint_as_float(w << 16); }
__device__ __forceinline__ float bf_hi(uint32_t w) { return __uint_as_float(w & 0xFFFF0000u); }
__device__ __forceinline__ float ex2(float x) { float y; asm("ex2.approx.ftz.f32 %0, %1;" : "=f"(y) : "f"(x)); return y; }
__device__ __forceinline__ uint4 lds128(uint32_t a) {
    uint4 v;
    asm volatile("ld.shared.v4.u32 {%0,%1,%2,%3}, [%4];" : "=r"(v.x), "=r"(v.y), "=r"(v.z), "=r"(v.w) : "r"(a) : "memory");
    return v;
}
__device__ __forceinline__ float2 lds64f(uint32_t a) {
    float2 v;
    asm volatile("ld.shared.v2.f32 {%0,%1}, [%2];" : "=f"(v.x), "=f"(v.y) : "r"(a) : "memory");
    return v;
}
__device__ __forceinline__ uint32_t lds32(uint32_t a) {
    uint32_t v;
    asm volatile("ld.shared.u32 %0, [%1];" : "=r"(v) : "r"(a) : "memory");
    return v;
}
__device__ __forceinline__ void sts128(uint32_t a, float x, float y, float z, float w) {
    asm volatile("st.shared.v4.f32 [%0], {%1,%2,%3,%4};" :: "r"(a), "f"(x), "f"(y), "f"(z), "f"(w) : "memory");
}
__device__ __forceinline__ void sts64(uint32_t a, uint32_t x, uint32_t y) {
    asm volatile("st.shared.v2.u32 [%0], {%1,%2};" :: "r"(a), "r"(x), "r"(y) : "memory");
}
__device__ __forceinline__ void sts32(uint32_t a, uint32_t x) {
    asm volatile("st.shared.u32 [%0], %1;" :: "r"(a), "r"(x) : "memory");
}
__device__ __forceinline__ void sts16(uint32_t a, uint32_t x) {
    asm volatile("st.shared.u16 [%0], %1;" :: "r"(a), "h"((unsigned short)x) : "memory");
}
__device__ __forceinline__ void fma8(float (&acc)[8], float s, const uint4& v) {
    acc[0] = fmaf(s, bf_lo(v.x), acc[0]); acc[1] = fmaf(s, bf_hi(v.x), acc[1]);
    acc[2] = fmaf(s, bf_lo(v.y), acc[2]); acc[3] = fmaf(s, bf_hi(v.y), acc[3]);
    acc[4] = fmaf(s, bf_lo(v.z), acc[4]); acc[5] = fmaf(s, bf_hi(v.z), acc[5]);
    acc[6] = fmaf(s, bf_lo(v.w), acc[6]); acc[7] = fmaf(s, bf_hi(v.w), acc[7]);
}
__device__ __forceinline__ float warp_max(float v) {
    int k = __float_as_int(v);
    k ^= (k >> 31) & 0x7FFFFFFF;
    asm("redux.sync.max.s32 %0, %0, 0xffffffff;" : "+r"(k));
    k ^= (k >> 31) & 0x7FFFFFFF;
    return __int_as_float(k);
}

#define T0_NS 1400
#define DT_NS 325
#define QGATE 1

__global__ void __launch_bounds__(NTHREADS, 1)
fused_kernel(const __grid_constant__ Params P)
{
    extern __shared__ unsigned char smem_raw[];
    const int tid = threadIdx.x;
    const int b = blockIdx.x;
    const int h = b >> 2, j = b & 3;
    const int r = b & 1, pp = (b >> 1) & 1;
    const int warp = tid >> 5, lane = tid & 31;
    const uint32_t sm = ((uint32_t)__cvta_generic_to_shared(smem_raw) + 1023u) & ~1023u;
    const bool ffn = h < 27;

    if (warp < 8) {
        const int g = lane >> 2, t = lane & 3;
        unsigned tag;
        unsigned* const e2slot = &g_e2[h * 256 + (4 * j + (warp >> 1)) * 16 + (g & 3) * 4 + 2 * (warp & 1) + (g >> 2)];
        {
            const int c16 = tid & 15;
            const int m0 = 160 * j + 10 * (tid >> 4);
            const __nv_bfloat16* wp = P.wq + (size_t)m0 * 4096 + h * 128 + c16 * 8;
            uint4 v[10];
#pragma unroll
            for (int i = 0; i < 10; i++) v[i] = ldg_stream(wp + i * 4096);
            tag = ld_poll1(&g_epoch);
            uint32_t xw[5];
#pragma unroll
            for (int i = 0; i < 5; i++) xw[i] = __ldg(reinterpret_cast<const uint32_t*>(P.x + m0) + i);
            asm volatile("barrier.cluster.arrive.relaxed.aligned;" ::: "memory");
            if (tid < 128) st_pub1(&g_e1[b * 128 + tid], tag & 1u);
            if (t == 0) st_pub1(e2slot, tag & 1u);
            tag = (tag + 1u) & 1u;
            float acc[8];
#pragma unroll
            for (int e = 0; e < 8; e++) acc[e] = 0.f;
#pragma unroll
            for (int i = 0; i < 10; i++) fma8(acc, (i & 1) ? bf_hi(xw[i >> 1]) : bf_lo(xw[i >> 1]), v[i]);
#pragma unroll
            for (int e = 0; e < 8; e++) acc[e] += __shfl_xor_sync(0xffffffffu, acc[e], 16);
            const bool up = lane >= 16;
            sts128(sm + SM_RED + warp * 512 + c16 * 32 + (lane & 16), up ? acc[4] : acc[0], up ? acc[5] : acc[1],
                   up ? acc[6] : acc[2], up ? acc[7] : acc[3]);
        }
        STAMP(0);
        bar_sync(1, 288);
        if (tid < 128) {
            float s = 0.f;
#pragma unroll
            for (int w = 0; w < 8; w++) s += __uint_as_float(lds32(sm + SM_RED + w * 512 + tid * 4));
            st_pub1(&g_e1[b * 128 + tid], tagf(s, tag));
            unsigned p[4];
            int it = 0;
#pragma unroll 1
            do {
#pragma unroll
                for (int s4 = 0; s4 < 4; s4++) p[s4] = ld_poll1(&g_e1[(4 * h + s4) * 128 + tid]);
            } while ((((p[0] ^ tag) | (p[1] ^ tag) | (p[2] ^ tag) | (p[3] ^ tag)) & 1u) && ++it < SPIN_MAX);
            const float q = (untagf(p[0]) + untagf(p[1])) + (untagf(p[2]) + untagf(p[3]));
            sts16(sm + SM_VF1 + ((tid >> 1) & 3) * 80 + (tid >> 4) * 8 + ((tid >> 3) & 1) * 4 + (tid & 1) * 2, pack_bf16(q, 0.f));
        }
        STAMP(1);
        bar_sync(2, 256);
        {
            uint4 qf[4];
#pragma unroll
            for (int i = 0; i < 4; i++) qf[i] = lds128(sm + SM_VF1 + t * 80 + i * 16);
            const int row = (warp & 1) * 16 + 2 * (lane & 7) + ((lane >> 3) & 1);
            const uint32_t base = sm + SM_WUK + (warp >> 1) * 8192 + row * 128 + (((lane >> 4) ^ (row & 7)) << 4);
            mbar_wait(sm + SM_BAR + 8 * (B_WUK + (warp >> 1)));
            uint32_t a[8][4];
#pragma unroll
            for (int s = 0; s < 8; s++) ldsm4((base + (s >> 2) * 4096) ^ ((s & 3) << 5), a[s]);
            float c[4][4];
#pragma unroll
            for (int i = 0; i < 4; i++) {
                c[i][0] = c[i][1] = c[i][2] = c[i][3] = 0.f;
                mma(c[i], a[2 * i][0], a[2 * i][1], a[2 * i][2], a[2 * i][3], qf[i].x, qf[i].y);
            }
#pragma unroll
            for (int i = 0; i < 4; i++) mma(c[i], a[2 * i + 1][0], a[2 * i + 1][1], a[2 * i + 1][2], a[2 * i + 1][3], qf[i].z, qf[i].w);
            const float sc = 0.08838834764831845f * 1.4426950408889634f;
            const float lo = ((c[0][0] + c[1][0]) + (c[2][0] + c[3][0])) * sc;
            const float hi = ((c[0][2] + c[1][2]) + (c[2][2] + c[3][2])) * sc;
            const uint32_t lob = (lo != lo) ? 0x7FFEu : (((__float_as_uint(lo) + 0x10000u) >> 16) & 0xFFFEu);
            if (t == 0) st_pub1(e2slot, (pack_bf16(0.f, hi) & 0xFFFF0000u) | lob | tag);
        }
        STAMP(2);
        {
            const int kq = warp >> 1, nh = warp & 1;
            uint4 qa[4];
            mbar_wait(sm + SM_BAR + 8 * (B_CKV + QGATE));
            {
                const unsigned* qp = &g_e2[(16 * pp + g) * 256 + (4 * r + kq) * 32 + t * 4];
                int it = 0;
                bool bad0 = true, bad1 = true;
#pragma unroll 1
                do {
                    if (bad0) { qa[0] = ld_poll4(qp); qa[1] = ld_poll4(qp + 16); }
                    if (bad1) { qa[2] = ld_poll4(qp + 8 * 256); qa[3] = ld_poll4(qp + 8 * 256 + 16); }
                    const unsigned ft = tag - 1u;
                    bad0 = !((qa[0].x ^ ft) & (qa[0].y ^ ft) & (qa[0].z ^ ft) & (qa[0].w ^ ft) & (qa[1].x ^ ft) & (qa[1].y ^ ft) & (qa[1].z ^ ft) & (qa[1].w ^ ft) & 1u);
                    bad1 = !((qa[2].x ^ ft) & (qa[2].y ^ ft) & (qa[2].z ^ ft) & (qa[2].w ^ ft) & (qa[3].x ^ ft) & (qa[3].y ^ ft) & (qa[3].z ^ ft) & (qa[3].w ^ ft) & 1u);
                } while ((bad0 | bad1) && ++it < SPIN_MAX);
#pragma unroll
                for (int i = 0; i < 4; i++) { qa[i].x &= ~1u; qa[i].y &= ~1u; qa[i].z &= ~1u; qa[i].w &= ~1u; }
            }
            __syncwarp();
            asm volatile("barrier.cluster.wait.aligned;" ::: "memory");
            STAMP(3);
            const uint32_t cbase = sm + SM_CKV + kq * 16384;
            mbar_wait(sm + SM_BAR + 8 * (B_CKV + kq));
            STAMP(4);
            {
                const uint32_t a0 = cbase + nh * 8192 + (lane & 7) * 128 + (((lane >> 3) ^ (lane & 7)) << 4);
                uint32_t bf[8][2][4];
#pragma unroll
                for (int n = 0; n < 8; n++) ldsm4(a0 + n * 1024, bf[n][0]);
#pragma unroll
                for (int n = 0; n < 8; n++) ldsm4((a0 + n * 1024) ^ 64, bf[n][1]);
                float s[8][4];
#pragma unroll
                for (int n = 0; n < 8; n++) {
                    s[n][0] = s[n][1] = s[n][2] = s[n][3] = 0.f;
                    mma(s[n], qa[0].x, qa[2].x, qa[0].y, qa[2].y, bf[n][0][0], bf[n][0][1]);
                }
#pragma unroll
                for (int n = 0; n < 8; n++) mma(s[n], qa[0].z, qa[2].z, qa[0].w, qa[2].w, bf[n][0][2], bf[n][0][3]);
#pragma unroll
                for (int n = 0; n < 8; n++) mma(s[n], qa[1].x, qa[3].x, qa[1].y, qa[3].y, bf[n][1][0], bf[n][1][1]);
#pragma unroll
                for (int n = 0; n < 8; n++) mma(s[n], qa[1].z, qa[3].z, qa[1].w, qa[3].w, bf[n][1][2], bf[n][1][3]);
                const uint32_t off = g * 256 + ((t ^ ((g & 1) << 2)) << 4);
                const uint32_t loc = sm + SM_WUK + kq * 8192 + nh * 2048 + off;
                const uint32_t rem = mapa(sm + SM_SPR + warp * 2048 + off, r ^ 1);
                const uint32_t rbar = mapa(sm + SM_BAR + 8 * B_SP, r ^ 1);
#pragma unroll
                for (int i = 0; i < 4; i++) {
                    const float* u = s[2 * i];
                    const float* v = s[2 * i + 1];
                    st_async4(rem ^ (i << 6), r ? u[0] : u[2], r ? u[1] : u[3], r ? v[0] : v[2], r ? v[1] : v[3], rbar);
                    sts128(loc ^ (i << 6), r ? u[2] : u[0], r ? u[3] : u[1], r ? v[2] : v[0], r ? v[3] : v[1]);
                }
            }
            uint32_t ct[4][4][4];
#pragma unroll
            for (int n = 0; n < 4; n++) {
                const uint32_t a = cbase + lane * 128 + (((4 * nh + n) ^ (lane & 7)) << 4);
#pragma unroll
                for (int kb = 0; kb < 4; kb++) ldsm4t(a + kb * 4096, ct[n][kb]);
            }
            bar_sync(2, 256);
            STAMP(5);
            mbar_wait_cluster(sm + SM_BAR + 8 * B_SP);
            STAMP(6);
            {
                const uint32_t o = (lane >> 4) * 2048 + warp * 256 + (((lane & 15) ^ ((warp & 1) << 2)) << 4);
                float s0 = 0.f, s1 = 0.f, s2 = 0.f, s3 = 0.f;
#pragma unroll
                for (int q = 0; q < 4; q++) {
                    const uint4 u = lds128(sm + SM_WUK + q * 8192 + o);
                    const uint4 v = lds128(sm + SM_SPR + q * 4096 + o);
                    s0 += __uint_as_float(u.x) + __uint_as_float(v.x); s1 += __uint_as_float(u.y) + __uint_as_float(v.y);
                    s2 += __uint_as_float(u.z) + __uint_as_float(v.z); s3 += __uint_as_float(u.w) + __uint_as_float(v.w);
                }
                const float m = warp_max(fmaxf(fmaxf(s0, s1), fmaxf(s2, s3)));
                const uint32_t p01 = pack_bf16(ex2(s0 - m), ex2(s1 - m));
                const uint32_t p23 = pack_bf16(ex2(s2 - m), ex2(s3 - m));
                const int s = lane >> 2;
                const uint32_t pa = sm + SM_P + (8 * r + warp) * 256 + t * 64 + (((s >> 1) ^ ((t >> 1) + 2 * (warp & 1))) << 4) + (s & 1) * 8;
                st_async2(mapa(pa, r ^ 1), p01, p23, mapa(sm + SM_BAR + 8 * B_P, r ^ 1));
                sts64(pa, p01, p23);
                bar_sync(2, 256);
                float l = (bf_lo(p01) + bf_hi(p01)) + (bf_lo(p23) + bf_hi(p23));
#pragma unroll
                for (int d = 1; d < 32; d <<= 1) l += __shfl_xor_sync(0xffffffffu, l, d);
                if (lane < 4) st_pub64(&g_st[((16 * pp + 8 * r + warp) * 32 + h) * 4 + lane], tagf(l, tag), __float_as_uint(m));
            }
            mbar_wait_cluster(sm + SM_BAR + 8 * B_P);
            STAMP(7);
            {
                float o[2][4][4];
#pragma unroll
                for (int n = 0; n < 4; n++)
#pragma unroll
                    for (int e = 0; e < 4; e++) o[0][n][e] = o[1][n][e] = 0.f;
                const uint32_t pa = sm + SM_P + g * 256 + t * 64 + (((t >> 1) + 2 * (g & 1)) << 4);
                uint4 pl[4], ph[4];
#pragma unroll
                for (int i = 0; i < 4; i++) { pl[i] = lds128(pa ^ (i << 4)); ph[i] = lds128((pa ^ (i << 4)) + 2048); }
#pragma unroll
                for (int i = 0; i < 4; i++) {
#pragma unroll
                    for (int n = 0; n < 4; n++) mma(o[0][n], pl[i].x, ph[i].x, pl[i].y, ph[i].y, ct[n][i][0], ct[n][i][1]);
#pragma unroll
                    for (int n = 0; n < 4; n++) mma(o[1][n], pl[i].z, ph[i].z, pl[i].w, ph[i].w, ct[n][i][2], ct[n][i][3]);
                }
                uint32_t w0[4], w1[4];
#pragma unroll
                for (int n = 0; n < 4; n++) {
                    w0[n] = pack_bf16(o[0][n][0] + o[1][n][0], o[0][n][1] + o[1][n][1]);
                    w1[n] = pack_bf16(o[0][n][2] + o[1][n][2], o[0][n][3] + o[1][n][3]);
                }
                uint4* op = &g_e3[(((16 * pp + g) * 32 + h) * 2 + r) * 32 + warp * 4 + t];
                st_pub2x64(op, tagw(w0[0], tag), w0[1], tagw(w0[2], tag), w0[3]);
                st_pub2x64(op + 8 * 32 * 2 * 32, tagw(w1[0], tag), w1[1], tagw(w1[2], tag), w1[3]);
            }
        }
        STAMP(8);
        if (ffn) {
            const int n = warp & 3, kh = warp >> 2;
            const uint32_t xa = sm + SM_XS + 320 * kh + 4 * t;
            uint32_t xa0[10], xa2[10];
#pragma unroll
            for (int s = 0; s < 10; s++) { xa0[s] = lds32(xa + s * 32); xa2[s] = lds32(xa + s * 32 + 16); }
            const uint32_t base = sm + SM_W1 + kh * 10240 + lane * 64 + ((n ^ ((lane >> 1) & 3)) << 4);
            mbar_wait(sm + SM_BAR + 8 * (B_W1 + kh));
            uint32_t bf[5][4];
#pragma unroll
            for (int i = 0; i < 5; i++) ldsm4t(base + i * 2048, bf[i]);
            float c0[4] = {0.f, 0.f, 0.f, 0.f}, c1[4] = {0.f, 0.f, 0.f, 0.f};
#pragma unroll
            for (int i = 0; i < 5; i++) {
                mma(c0, xa0[2 * i], 0u, xa2[2 * i], 0u, bf[i][0], bf[i][1]);
                mma(c1, xa0[2 * i + 1], 0u, xa2[2 * i + 1], 0u, bf[i][2], bf[i][3]);
            }
            if (g == 0)
                st_async2(mapa(sm + SM_XH + (2 * r + kh) * 64 + (n & 1) * 32 + t * 8, n >> 1), __float_as_uint(c0[0] + c1[0]),
                          __float_as_uint(c0[1] + c1[1]), mapa(sm + SM_BAR + 8 * B_XH, n >> 1));
        }
        STAMP(9);
        {
            uint4 v[4];
            uint2 st[4];
            const uint4* dp = &g_e3[((h * 32 + 4 * warp) * 2 + r) * 32 + lane];
            const uint2* sp = &g_st[(h * 32 + 4 * warp) * 4];
            bool bad[4] = {true, true, true, true};
            int it = 0;
            bool any;
#pragma unroll 1
            do {
#pragma unroll
                for (int i = 0; i < 4; i++)
                    if (bad[i]) { v[i] = ld_poll2x64(dp + i * 64); st[i] = ld_poll64(sp + i * 4); }
                any = false;
#pragma unroll
                for (int i = 0; i < 4; i++) { bad[i] = ((v[i].x ^ tag) | (v[i].z ^ tag) | (st[i].x ^ tag)) & 1u; any |= bad[i]; }
            } while (any && ++it < SPIN_MAX);
            STAMP(10);
            const float m = fmaxf(fmaxf(__uint_as_float(st[0].y), __uint_as_float(st[1].y)), fmaxf(__uint_as_float(st[2].y), __uint_as_float(st[3].y)));
            float acc[8], l = 0.f;
#pragma unroll
            for (int e = 0; e < 8; e++) acc[e] = 0.f;
#pragma unroll
            for (int i = 0; i < 4; i++) {
                const float f = ex2(__uint_as_float(st[i].y) - m);
                l = fmaf(f, untagf(st[i].x), l);
                v[i].x &= ~1u; v[i].z &= ~1u;
                fma8(acc, f, v[i]);
            }
            sts128(sm + SM_RED + warp * 1024 + lane * 16, acc[0], acc[1], acc[2], acc[3]);
            sts128(sm + SM_RED + warp * 1024 + 512 + lane * 16, acc[4], acc[5], acc[6], acc[7]);
            if (lane == 0) sts64(sm + SM_ML + warp * 8, __float_as_uint(m), __float_as_uint(l));
        }
        bar_sync(2, 256);
        {
            uint4 ml[4];
            float rv[8];
#pragma unroll
            for (int i = 0; i < 4; i++) ml[i] = lds128(sm + SM_ML + i * 16);
#pragma unroll
            for (int w = 0; w < 8; w++) rv[w] = __uint_as_float(lds32(sm + SM_RED + w * 1024 + tid * 4));
            float M = __uint_as_float(ml[0].x);
#pragma unroll
            for (int i = 0; i < 4; i++) M = fmaxf(M, fmaxf(__uint_as_float(ml[i].x), __uint_as_float(ml[i].z)));
            float L = 0.f, s = 0.f;
#pragma unroll
            for (int i = 0; i < 4; i++) {
                const float f0 = ex2(__uint_as_float(ml[i].x) - M), f1 = ex2(__uint_as_float(ml[i].z) - M);
                L = fmaf(f0, __uint_as_float(ml[i].y), L);
                L = fmaf(f1, __uint_as_float(ml[i].w), L);
                s = fmaf(f0, rv[2 * i], s);
                s = fmaf(f1, rv[2 * i + 1], s);
            }
            s = __fdividef(s, L);
            const uint32_t hi = pack_bf16(s, 0.f);
            const uint32_t lo = pack_bf16(s - bf_lo(hi), 0.f);
            const uint32_t o = sm + SM_VF3 + ((tid >> 2) & 3) * 144 + ((tid >> 4) & 7) * 16 + (tid >> 7) * 8 + (tid & 3) * 2;
            sts16(o, hi);
            sts16(o + 576, lo);
        }
        {
            uint32_t bf[8][4];
            const uint32_t base = sm + SM_WUV + lane * 128 + ((warp ^ (lane & 7)) << 4);
#pragma unroll
            for (int i = 0; i < 4; i++) {
                mbar_wait(sm + SM_BAR + 8 * (B_WUV + i));
                ldsm4t(base + i * 8192, bf[2 * i]);
                ldsm4t(base + i * 8192 + 4096, bf[2 * i + 1]);
            }
            bar_sync(2, 256);
            STAMP(11);
            uint4 hi[8], lo[8];
#pragma unroll
            for (int i = 0; i < 8; i++) { hi[i] = lds128(sm + SM_VF3 + t * 144 + i * 16); lo[i] = lds128(sm + SM_VF3 + 576 + t * 144 + i * 16); }
            float c[4][4];
#pragma unroll
            for (int i = 0; i < 4; i++) c[i][0] = c[i][1] = c[i][2] = c[i][3] = 0.f;
#pragma unroll
            for (int i = 0; i < 8; i++) {
                mma(c[(2 * i) & 3], hi[i].x, lo[i].x, hi[i].y, lo[i].y, bf[i][0], bf[i][1]);
                mma(c[(2 * i + 1) & 3], hi[i].z, lo[i].z, hi[i].w, lo[i].w, bf[i][2], bf[i][3]);
            }
            const float v0 = ((c[0][0] + c[1][0]) + (c[2][0] + c[3][0])) + ((c[0][2] + c[1][2]) + (c[2][2] + c[3][2]));
            const float v1 = ((c[0][1] + c[1][1]) + (c[2][1] + c[3][1])) + ((c[0][3] + c[1][3]) + (c[2][3] + c[3][3]));
            if (g == 0)
                st_async2(mapa(sm + SM_XC + r * 128 + (warp & 3) * 32 + t * 8, warp >> 2), __float_as_uint(v0), __float_as_uint(v1),
                          mapa(sm + SM_BAR + 8 * B_XC, warp >> 2));
        }
        STAMP(12);
        {
            float c[10][4];
#pragma unroll
            for (int n = 0; n < 10; n++) c[n][0] = c[n][1] = c[n][2] = c[n][3] = 0.f;
            const int half = warp >> 2;
            uint32_t off[5];
#pragma unroll
            for (int i = 0; i < 5; i++) {
                const int N = 10 * (warp & 3) + 2 * i + (lane >> 4);
                off[i] = sm + half * 10240 + (N >> 3) * 2048 + (lane & 15) * 128 + (((N & 7) ^ (lane & 7)) << 4);
            }
            if (ffn) {
                mbar_wait_cluster(sm + SM_BAR + 8 * B_XH);
                uint32_t a[2];
#pragma unroll
                for (int q = 0; q < 2; q++) {
                    float2 u[4];
#pragma unroll
                    for (int s4 = 0; s4 < 4; s4++) u[s4] = lds64f(sm + SM_XH + s4 * 64 + q * 32 + t * 8);
                    const uint32_t hb = pack_bf16((u[0].x + u[1].x) + (u[2].x + u[3].x), (u[0].y + u[1].y) + (u[2].y + u[3].y));
                    const float h0 = bf_lo(hb), h1 = bf_hi(hb);
                    a[q] = pack_bf16(__fdividef(h0, 1.f + __expf(-h0)), __fdividef(h1, 1.f + __expf(-h1)));
                }
                mbar_wait(sm + SM_BAR + 8 * (B_W2 + half));
                uint32_t bf[5][4];
#pragma unroll
                for (int i = 0; i < 5; i++) ldsm4t(off[i] + SM_W2, bf[i]);
#pragma unroll
                for (int i = 0; i < 5; i++) {
                    mma(c[2 * i], 0u, a[0], 0u, a[1], bf[i][0], bf[i][1]);
                    mma(c[2 * i + 1], 0u, a[0], 0u, a[1], bf[i][2], bf[i][3]);
                }
            }
            const float gt = __uint_as_float(lds32(sm + SM_G));
            mbar_wait_cluster(sm + SM_BAR + 8 * B_XC);
            STAMP(13);
            uint32_t ca[4];
#pragma unroll
            for (int q = 0; q < 4; q++) {
                const float2 u = lds64f(sm + SM_XC + q * 32 + t * 8), v = lds64f(sm + SM_XC + 128 + q * 32 + t * 8);
                ca[q] = pack_bf16(u.x + v.x, u.y + v.y);
            }
#pragma unroll
            for (int s = 0; s < 2; s++) {
                mbar_wait(sm + SM_BAR + 8 * (B_WO + 2 * s + half));
                uint32_t bf[5][4];
#pragma unroll
                for (int i = 0; i < 5; i++) ldsm4t(off[i] + SM_WO + s * 20480, bf[i]);
#pragma unroll
                for (int i = 0; i < 5; i++) {
                    mma(c[2 * i], ca[2 * s], 0u, ca[2 * s + 1], 0u, bf[i][0], bf[i][1]);
                    mma(c[2 * i + 1], ca[2 * s], 0u, ca[2 * s + 1], 0u, bf[i][2], bf[i][3]);
                }
            }
            STAMP(14);
            if (g == 0) {
                unsigned* op = reinterpret_cast<unsigned*>(g_e4) + ((10 * warp) * NCTA + b) * 8 + 2 * t;
#pragma unroll
                for (int n = 0; n < 10; n++)
                    st_pub64(op + n * NCTA * 8, tagf(gt * c[n][0] + (1.f - gt) * c[n][2], tag),
                             __float_as_uint(gt * c[n][1] + (1.f - gt) * c[n][3]));
            }
        }
        STAMP(15);
    } else {
        const unsigned t0 = gtimer();
        const uint32_t bar = sm + SM_BAR + 8 * lane;
        asm volatile("mbarrier.init.shared::cta.b64 [%0], 1;" :: "r"(bar) : "memory");
        if (lane >= B_SP) {
            const uint32_t tx = lane == B_SP ? 16384u : lane == B_P ? 2048u : 256u;
            asm volatile("mbarrier.arrive.expect_tx.shared::cta.b64 _, [%0], %1;" :: "r"(bar), "r"(tx) : "memory");
        }
        asm volatile("fence.mbarrier_init.release.cluster;" ::: "memory");
        asm volatile("barrier.cluster.arrive.relaxed.aligned;" ::: "memory");
        if (lane < 6) asm volatile("prefetch.tensormap [%0];" :: "l"(&P.m[lane]) : "memory");
        const unsigned epoch = ld_poll1(&g_epoch);
        {
            uint32_t xw[10], gw[10];
#pragma unroll
            for (int i = 0; i < 10; i++) {
                xw[i] = __ldg(reinterpret_cast<const uint32_t*>(P.x) + i * 32 + lane);
                gw[i] = __ldg(reinterpret_cast<const uint32_t*>(P.gate) + i * 32 + lane);
            }
            float z = 0.f;
#pragma unroll
            for (int i = 0; i < 10; i++) {
                if ((i >= 5) == (r != 0)) sts32(sm + SM_XS + ((i % 5) * 32 + lane) * 4, xw[i]);
                z = fmaf(bf_lo(xw[i]), bf_lo(gw[i]), z);
                z = fmaf(bf_hi(xw[i]), bf_hi(gw[i]), z);
            }
#pragma unroll
            for (int d = 1; d < 32; d <<= 1) z += __shfl_xor_sync(0xffffffffu, z, d);
            if (lane == 0) sts32(sm + SM_G, __float_as_uint(1.f / (1.f + __expf(-z))));
        }
#pragma unroll
        for (int i = 0; i < 5; i++)
            st_pub2x64(&g_e4[((i * 16 + (lane >> 1)) * NCTA + b) * 2 + (lane & 1)], epoch & 1u, 0u, epoch & 1u, 0u);
        bar_arrive(1, 288);
        {
            int map, c0 = 0, c1, c2;
            uint32_t dst, bytes, due;
            const int k = lane;
            constexpr int DF = DT_NS * 135 / 128;
            if (k < B_CKV)      { map = 0; c1 = 128 * j + 32 * k;            c2 = 2 * h;              dst = SM_WUK + k * 8192;            bytes = 8192;  due = k * DT_NS; }
            else if (k < B_W1)  { map = 1; c1 = 128 * h;                     c2 = 4 * r + k - B_CKV;  dst = SM_CKV + (k - B_CKV) * 16384; bytes = 16384; due = k * DT_NS; }
            else if (k < B_WUV) { map = 2; c1 = 320 * r + 160 * (k - B_W1);  c2 = h; c0 = 32 * pp;    dst = SM_W1 + (k - B_W1) * 10240;   bytes = ffn ? 10240 : 0; due = 8 * DT_NS + (k - B_W1) * DF; }
            else if (k < B_W2)  { map = 3; c1 = 256 * r + 64 * (k - B_WUV);  c2 = 2 * h + pp;         dst = SM_WUV + (k - B_WUV) * 8192;  bytes = 8192;  due = (k - 2) * DT_NS + 2 * DF; }
            else if (k < B_WO)  { map = 4; c1 = 16 * b;                      c2 = 5 * (k - B_W2);     dst = SM_W2 + (k - B_W2) * 10240;   bytes = ffn ? 10240 : 0; due = 12 * DT_NS + (k - 12) * DF; }
            else                { map = 5; c1 = 32 * b + 16 * ((k - B_WO) >> 1); c2 = 5 * (k & 1);    dst = SM_WO + (k - B_WO) * 10240;   bytes = k < B_SP ? 10240 : 0;
                                  due = 12 * DT_NS + 4 * DF + (k - B_WO) * (DT_NS * 5 / 4); }
            due += T0_NS;
            bool pending = bytes != 0;
            while (__any_sync(0xffffffffu, pending)) {
                const unsigned now = gtimer() - t0;
                if (pending && now >= due) {
                    asm volatile("mbarrier.arrive.expect_tx.shared::cta.b64 _, [%0], %1;" :: "r"(bar), "r"(bytes) : "memory");
                    asm volatile("cp.async.bulk.tensor.3d.shared::cluster.global.mbarrier::complete_tx::bytes [%0], [%1, {%3,%4,%5}], [%2];"
                                 :: "r"(sm + dst), "l"(&P.m[map]), "r"(bar), "r"(c0), "r"(c1), "r"(c2) : "memory");
                    pending = false;
                }
            }
        }
        if (b < 80) {
            const unsigned tag = (epoch + 1u) & 1u;
            mbar_wait(sm + SM_BAR + 8 * (B_WO + 3));
            mbar_wait(sm + SM_BAR + 8 * B_XC);
            STAMP_T(256, 16);
            const uint4* p = &g_e4[b * NCTA * 2 + lane];
            uint4 v[8];
            bool bad[8];
#pragma unroll
            for (int i = 0; i < 8; i++) bad[i] = true;
            int it = 0;
            bool any;
#pragma unroll 1
            do {
#pragma unroll
                for (int i = 0; i < 8; i++) if (bad[i]) v[i] = ld_poll2x64(p + i * 32);
                any = false;
#pragma unroll
                for (int i = 0; i < 8; i++) { bad[i] = ((v[i].x ^ tag) | (v[i].z ^ tag)) & 1u; any |= bad[i]; }
            } while (any && ++it < SPIN_MAX);
            __syncwarp();
            float s0 = 0.f, s1 = 0.f, s2 = 0.f, s3 = 0.f;
#pragma unroll
            for (int i = 0; i < 8; i++) {
                s0 += untagf(v[i].x); s1 += __uint_as_float(v[i].y);
                s2 += untagf(v[i].z); s3 += __uint_as_float(v[i].w);
            }
#pragma unroll
            for (int d = 2; d < 32; d <<= 1) {
                s0 += __shfl_xor_sync(0xffffffffu, s0, d); s1 += __shfl_xor_sync(0xffffffffu, s1, d);
                s2 += __shfl_xor_sync(0xffffffffu, s2, d); s3 += __shfl_xor_sync(0xffffffffu, s3, d);
            }
            if (lane < 2) *reinterpret_cast<uint2*>(P.out + b * 8 + lane * 4) = make_uint2(pack_bf16(s0, s1), pack_bf16(s2, s3));
            if (b == 0 && lane == 0) st_pub1(&g_epoch, epoch + 1u);
            STAMP_T(256, 17);
        }
    }
}

typedef CUresult (*EncodeFn)(CUtensorMap*, CUtensorMapDataType, cuuint32_t, void*, const cuuint64_t*, const cuuint64_t*,
                             const cuuint32_t*, const cuuint32_t*, CUtensorMapInterleave, CUtensorMapSwizzle,
                             CUtensorMapL2promotion, CUtensorMapFloatOOBfill);

void make_map(EncodeFn enc, CUtensorMap* m, const void* base, int rows, int cols, int box_cols, int box_rows, int box_blks) {
    cuuint64_t gd[3] = {64, (cuuint64_t)rows, (cuuint64_t)(cols / 64)};
    cuuint64_t gs[2] = {(cuuint64_t)cols * 2, 128};
    cuuint32_t bd[3] = {(cuuint32_t)box_cols, (cuuint32_t)box_rows, (cuuint32_t)box_blks};
    cuuint32_t es[3] = {1, 1, 1};
    enc(m, CU_TENSOR_MAP_DATA_TYPE_BFLOAT16, 3, const_cast<void*>(base), gd, gs, bd, es, CU_TENSOR_MAP_INTERLEAVE_NONE,
        box_cols == 64 ? CU_TENSOR_MAP_SWIZZLE_128B : CU_TENSOR_MAP_SWIZZLE_64B,
        box_cols == 64 ? CU_TENSOR_MAP_L2_PROMOTION_NONE : CU_TENSOR_MAP_L2_PROMOTION_L2_128B, CU_TENSOR_MAP_FLOAT_OOB_FILL_NONE);
}

}

extern "C" void kernel_launch(void* const* d_in, const int* in_sizes, int n_in, void* d_out, int out_size) {
    (void)in_sizes; (void)n_in; (void)out_size;
    static EncodeFn enc = nullptr;
    if (!enc) {
        void* fn = nullptr;
        cudaDriverEntryPointQueryResult st;
        cudaGetDriverEntryPoint("cuTensorMapEncodeTiled", &fn, cudaEnableDefault, &st);
        enc = (EncodeFn)fn;
        cudaFuncSetAttribute(fused_kernel, cudaFuncAttributeMaxDynamicSharedMemorySize, SMEM_BYTES);
    }
    Params p;
    make_map(enc, &p.m[0], d_in[3], 512, 4096, 64, 32, 2);
    make_map(enc, &p.m[1], d_in[1], 4096, 512, 64, 128, 1);
    make_map(enc, &p.m[2], d_in[7], 640, 1728, 32, 160, 1);
    make_map(enc, &p.m[3], d_in[4], 512, 4096, 64, 64, 1);
    make_map(enc, &p.m[4], d_in[8], 1728, 640, 64, 16, 5);
    make_map(enc, &p.m[5], d_in[5], 4096, 640, 64, 16, 5);
    p.x = (const __nv_bfloat16*)d_in[0];
    p.wq = (const __nv_bfloat16*)d_in[2];
    p.gate = (const __nv_bfloat16*)d_in[9];
    p.out = (__nv_bfloat16*)d_out;

    cudaLaunchConfig_t cfg = {};
    cfg.gridDim = dim3(NCTA);
    cfg.blockDim = dim3(NTHREADS);
    cfg.dynamicSmemBytes = SMEM_BYTES;
    cfg.stream = cudaStreamPerThread;
    cudaLaunchAttribute at[1];
    at[0].id = cudaLaunchAttributeClusterDimension;
    at[0].val.clusterDim.x = 2;
    at[0].val.clusterDim.y = 1;
    at[0].val.clusterDim.z = 1;
    cfg.attrs = at;
    cfg.numAttrs = 1;
    cudaLaunchKernelEx(&cfg, fused_kernel, p);
}
```

```cpp
#include <cuda_runtime.h>
#include <cuda.h>
#include <cuda_bf16.h>
#include <stdint.h>

namespace {

constexpr int NCTA = 128;
constexpr int NTHREADS = 320;
constexpr int SPIN_MAX = 1 << 18;

constexpr int SM_WUK = 0;
constexpr int SM_CKV = SM_WUK + 32768;
constexpr int SM_WUV = SM_CKV + 65536;
constexpr int SM_W1  = SM_WUV + 32768;
constexpr int SM_W2  = SM_W1 + 20480;
constexpr int SM_WO  = SM_W2 + 20480;
constexpr int SM_SPR = SM_WO + 40960;
constexpr int SM_RED = SM_SPR;
constexpr int SM_VF3 = SM_SPR + 8192;
constexpr int SM_P   = SM_WUK + 4096;
constexpr int SM_VF1 = SM_SPR + 16384;
constexpr int SM_XS  = SM_VF1 + 320;
constexpr int SM_XC  = SM_XS + 640;
constexpr int SM_XH  = SM_XC + 512;
constexpr int SM_G   = SM_XH + 512;
constexpr int SM_BAR = SM_G + 32;
constexpr int SM_END = SM_BAR + 32 * 8;
constexpr int SMEM_BYTES = SM_END;
static_assert(SMEM_BYTES <= 232448 - 256, "smem");

constexpr int B_WUK = 0, B_CKV = 4, B_W1 = 8, B_WUV = 10, B_W2 = 14, B_WO = 16, B_SP = 20, B_P = 21, B_XC = 22, B_XH = 23;

struct Scratch {
    uint4    e3[32 * 2 * 8 * 32 * 4];
    uint4    e4[80 * NCTA * 2];
    unsigned e1[NCTA * 128];
    uint4    e2[2 * 2 * 16 * 32];
    uint2    st[32 * 32 * 4];
    unsigned epoch;
};
__device__ __align__(1024) Scratch g_s;

struct Params {
    const __nv_bfloat16* wq;
    const __nv_bfloat16* x;
    Scratch* s;
    const __nv_bfloat16* gate;
    __nv_bfloat16* out;
    alignas(64) CUtensorMap m[6];
};

#define STAMP(i)
#define STAMP_T(t, i)

__device__ __forceinline__ unsigned clock32() { unsigned c; asm volatile("mov.u32 %0, %%clock;" : "=r"(c) :: "memory"); return c; }
__device__ __forceinline__ unsigned gtimer() { unsigned c; asm volatile("mov.u32 %0, %%globaltimer_lo;" : "=r"(c) :: "memory"); return c; }

__device__ __forceinline__ uint4 ldg_stream(const void* p) {
    uint4 v;
    asm volatile("ld.global.nc.L1::no_allocate.v4.u32 {%0,%1,%2,%3}, [%4];"
                 : "=r"(v.x), "=r"(v.y), "=r"(v.z), "=r"(v.w) : "l"(p));
    return v;
}
__device__ __forceinline__ uint4 ld_poll4(const void* p) {
    uint4 v;
    asm volatile("ld.relaxed.gpu.global.v4.u32 {%0,%1,%2,%3}, [%4];"
                 : "=r"(v.x), "=r"(v.y), "=r"(v.z), "=r"(v.w) : "l"(p) : "memory");
    return v;
}
__device__ __forceinline__ uint4 ld_poll2x64(const void* p) {
    uint4 v;
    asm volatile("{.reg .b64 a, b; ld.relaxed.gpu.global.v2.b64 {a, b}, [%4]; mov.b64 {%0,%1}, a; mov.b64 {%2,%3}, b;}"
                 : "=r"(v.x), "=r"(v.y), "=r"(v.z), "=r"(v.w) : "l"(p) : "memory");
    return v;
}
__device__ __forceinline__ uint2 ld_poll64(const void* p) {
    uint2 v;
    asm volatile("{.reg .b64 a; ld.relaxed.gpu.global.b64 a, [%2]; mov.b64 {%0,%1}, a;}" : "=r"(v.x), "=r"(v.y) : "l"(p) : "memory");
    return v;
}
__device__ __forceinline__ unsigned ld_poll1(const void* p) {
    unsigned v;
    asm volatile("ld.relaxed.gpu.global.u32 %0, [%1];" : "=r"(v) : "l"(p) : "memory");
    return v;
}
__device__ __forceinline__ void st_pub2x64(void* p, unsigned a, unsigned b, unsigned c, unsigned d) {
    asm volatile("{.reg .b64 x, y; mov.b64 x, {%1,%2}; mov.b64 y, {%3,%4}; st.relaxed.gpu.global.v2.b64 [%0], {x, y};}"
                 :: "l"(p), "r"(a), "r"(b), "r"(c), "r"(d) : "memory");
}
__device__ __forceinline__ void st_pub64(void* p, unsigned a, unsigned b) {
    asm volatile("{.reg .b64 x; mov.b64 x, {%1,%2}; st.relaxed.gpu.global.b64 [%0], x;}" :: "l"(p), "r"(a), "r"(b) : "memory");
}
__device__ __forceinline__ void st_pub1(void* p, unsigned a) {
    asm volatile("st.relaxed.gpu.global.u32 [%0], %1;" :: "l"(p), "r"(a) : "memory");
}
__device__ __forceinline__ unsigned tagw(unsigned w, unsigned tag) { return (w & ~1u) | tag; }
__device__ __forceinline__ unsigned tagf(float v, unsigned tag) { return (__float_as_uint(v) & ~1u) | tag; }
__device__ __forceinline__ float untagf(unsigned w) { return __uint_as_float(w & ~1u); }

__device__ __forceinline__ void mbar_wait(uint32_t bar) {
    uint32_t ok;
    int it = 0;
#pragma unroll 1
    do {
        asm volatile("{.reg .pred p; mbarrier.try_wait.parity.shared::cta.b64 p, [%1], 0; selp.u32 %0,1,0,p;}"
                     : "=r"(ok) : "r"(bar) : "memory");
    } while (!ok && ++it < SPIN_MAX);
}
__device__ __forceinline__ void bar_sync(int id, int n) { asm volatile("bar.sync %0, %1;" :: "r"(id), "r"(n) : "memory"); }
__device__ __forceinline__ void bar_arrive(int id, int n) { asm volatile("bar.arrive %0, %1;" :: "r"(id), "r"(n) : "memory"); }
__device__ __forceinline__ uint32_t mapa(uint32_t a, uint32_t rank) {
    uint32_t r;
    asm("mapa.shared::cluster.u32 %0, %1, %2;" : "=r"(r) : "r"(a), "r"(rank));
    return r;
}
__device__ __forceinline__ void st_async4(uint32_t a, float x, float y, float z, float w, uint32_t bar) {
    asm volatile("st.async.weak.shared::cluster.mbarrier::complete_tx::bytes.v4.f32 [%0], {%1,%2,%3,%4}, [%5];"
                 :: "r"(a), "f"(x), "f"(y), "f"(z), "f"(w), "r"(bar) : "memory");
}
__device__ __forceinline__ void st_async2(uint32_t a, uint32_t x, uint32_t y, uint32_t bar) {
    asm volatile("st.async.weak.shared::cluster.mbarrier::complete_tx::bytes.v2.b32 [%0], {%1,%2}, [%3];"
                 :: "r"(a), "r"(x), "r"(y), "r"(bar) : "memory");
}

__device__ __forceinline__ void ldsm4(uint32_t a, uint32_t (&r)[4]) {
    asm volatile("ldmatrix.sync.aligned.m8n8.x4.shared.b16 {%0,%1,%2,%3}, [%4];"
                 : "=r"(r[0]), "=r"(r[1]), "=r"(r[2]), "=r"(r[3]) : "r"(a) : "memory");
}
__device__ __forceinline__ void ldsm4t(uint32_t a, uint32_t (&r)[4]) {
    asm volatile("ldmatrix.sync.aligned.m8n8.x4.trans.shared.b16 {%0,%1,%2,%3}, [%4];"
                 : "=r"(r[0]), "=r"(r[1]), "=r"(r[2]), "=r"(r[3]) : "r"(a) : "memory");
}
__device__ __forceinline__ void mma(float (&c)[4], uint32_t a0, uint32_t a1, uint32_t a2, uint32_t a3, uint32_t b0, uint32_t b1) {
    asm("mma.sync.aligned.m16n8k16.row.col.f32.bf16.bf16.f32 {%0,%1,%2,%3}, {%4,%5,%6,%7}, {%8,%9}, {%0,%1,%2,%3};"
        : "+f"(c[0]), "+f"(c[1]), "+f"(c[2]), "+f"(c[3])
        : "r"(a0), "r"(a1), "r"(a2), "r"(a3), "r"(b0), "r"(b1));
}
__device__ __forceinline__ uint32_t pack_bf16(float lo, float hi) {
    uint32_t r;
    asm("cvt.rn.bf16x2.f32 %0, %1, %2;" : "=r"(r) : "f"(hi), "f"(lo));
    return r;
}
__device__ __forceinline__ float bf_lo(uint32_t w) { return __uint_as_float(w << 16); }
__device__ __forceinline__ float bf_hi(uint32_t w) { return __uint_as_float(w & 0xFFFF0000u); }
__device__ __forceinline__ float ex2(float x) { float y; asm("ex2.approx.ftz.f32 %0, %1;" : "=f"(y) : "f"(x)); return y; }
__device__ __forceinline__ uint4 lds128(uint32_t a) {
    uint4 v;
    asm volatile("ld.shared.v4.u32 {%0,%1,%2,%3}, [%4];" : "=r"(v.x), "=r"(v.y), "=r"(v.z), "=r"(v.w) : "r"(a) : "memory");
    return v;
}
__device__ __forceinline__ float2 lds64f(uint32_t a) {
    float2 v;
    asm volatile("ld.shared.v2.f32 {%0,%1}, [%2];" : "=f"(v.x), "=f"(v.y) : "r"(a) : "memory");
    return v;
}
__device__ __forceinline__ uint32_t lds32(uint32_t a) {
    uint32_t v;
    asm volatile("ld.shared.u32 %0, [%1];" : "=r"(v) : "r"(a) : "memory");
    return v;
}
__device__ __forceinline__ void sts128(uint32_t a, float x, float y, float z, float w) {
    asm volatile("st.shared.v4.f32 [%0], {%1,%2,%3,%4};" :: "r"(a), "f"(x), "f"(y), "f"(z), "f"(w) : "memory");
}
__device__ __forceinline__ void sts64(uint32_t a, uint32_t x, uint32_t y) {
    asm volatile("st.shared.v2.u32 [%0], {%1,%2};" :: "r"(a), "r"(x), "r"(y) : "memory");
}
__device__ __forceinline__ void sts32(uint32_t a, uint32_t x) {
    asm volatile("st.shared.u32 [%0], %1;" :: "r"(a), "r"(x) : "memory");
}
__device__ __forceinline__ void sts16(uint32_t a, uint32_t x) {
    asm volatile("st.shared.u16 [%0], %1;" :: "r"(a), "h"((unsigned short)x) : "memory");
}
__device__ __forceinline__ void fma8(float (&acc)[8], float s, const uint4& v) {
    acc[0] = fmaf(s, bf_lo(v.x), acc[0]); acc[1] = fmaf(s, bf_hi(v.x), acc[1]);
    acc[2] = fmaf(s, bf_lo(v.y), acc[2]); acc[3] = fmaf(s, bf_hi(v.y), acc[3]);
    acc[4] = fmaf(s, bf_lo(v.z), acc[4]); acc[5] = fmaf(s, bf_hi(v.z), acc[5]);
    acc[6] = fmaf(s, bf_lo(v.w), acc[6]); acc[7] = fmaf(s, bf_hi(v.w), acc[7]);
}
__device__ __forceinline__ float warp_max(float v) {
    int k = __float_as_int(v);
    k ^= (k >> 31) & 0x7FFFFFFF;
    asm("redux.sync.max.s32 %0, %0, 0xffffffff;" : "+r"(k));
    k ^= (k >> 31) & 0x7FFFFFFF;
    return __int_as_float(k);
}

__device__ __forceinline__ void st_async1(uint32_t a, float x, uint32_t bar) {
    asm volatile("st.async.weak.shared::cluster.mbarrier::complete_tx::bytes.f32 [%0], %1, [%2];" :: "r"(a), "f"(x), "r"(bar) : "memory");
}
__device__ __forceinline__ void st_pub4(void* p, unsigned a, unsigned b, unsigned c, unsigned d) {
    asm volatile("st.relaxed.gpu.global.v4.u32 [%0], {%1,%2,%3,%4};" :: "l"(p), "r"(a), "r"(b), "r"(c), "r"(d) : "memory");
}
__device__ __forceinline__ uint32_t ldg32(const void* p) {
    uint32_t v;
    asm volatile("ld.global.nc.u32 %0, [%1];" : "=r"(v) : "l"(p));
    return v;
}
__device__ __forceinline__ void mma4(float (&c)[4], const uint32_t (&a)[4], uint32_t b0, uint32_t b1) { mma(c, a[0], a[1], a[2], a[3], b0, b1); }
__device__ __forceinline__ float shfl_x(float v, int m) { return __shfl_xor_sync(0xffffffffu, v, m); }
#define PIN(x) asm volatile("" : "+r"(x))
#define PINL(x) asm volatile("" : "+l"(x))

#define T0_NS 1400
#define DT_NS 325
#define QGATE 1
#define BACKOFF 64

__global__ void __cluster_dims__(2, 1, 1) __launch_bounds__(NTHREADS, 1)
fused_kernel(const __grid_constant__ Params P)
{
    extern __shared__ __align__(1024) unsigned char smem_raw[];
    const int tid = threadIdx.x;
    const int b = blockIdx.x;
    const int h = b >> 2, j = b & 3;
    uint4 wv[10];
    uint32_t xw[5];
    if (tid < 256) {
        const int m0 = 160 * j + 10 * (tid >> 4);
        const __nv_bfloat16* wp = P.wq + (size_t)m0 * 4096 + h * 128 + (tid & 15) * 8;
#pragma unroll
        for (int i = 0; i < 10; i++) wv[i] = ldg_stream(wp + i * 4096);
#pragma unroll
        for (int i = 0; i < 5; i++) xw[i] = ldg32(P.x + m0 + 2 * i);
    }
    const int r = b & 1, pp = (b >> 1) & 1;
    const int warp = tid >> 5, lane = tid & 31;
    const uint32_t sm = (uint32_t)__cvta_generic_to_shared(smem_raw);
    const bool ffn = h < 27;
    Scratch* const S = P.s;

    if (warp < 8) {
        asm volatile("barrier.cluster.arrive.relaxed.aligned;" ::: "memory");
        const int g = lane >> 2, t = lane & 3, l7 = lane & 7;
        const int kq = warp >> 1, nh = warp & 1;
        const uint32_t smp = mapa(sm, r ^ 1);
        const int row1 = nh * 16 + 2 * l7 + ((lane >> 3) & 1);
        uint32_t a_wuk = sm + SM_WUK + kq * 8192 + row1 * 128 + (((lane >> 4) ^ (row1 & 7)) << 4);
        unsigned* p_e2w = reinterpret_cast<unsigned*>(S->e2) +
                          (((((h >> 4) * 2 + pp) * 16 + 8 * r + warp) * 32) + (h & 7) * 4 + (g & 3)) * 4 + (((h >> 3) & 1) ^ pp) + 2 * (g >> 2);
        const uint4* p_e2r = S->e2 + ((pp * 2 + r) * 16 + kq * 4) * 32 + lane;
        uint32_t a_s = sm + SM_CKV + kq * 16384 + nh * 8192 + l7 * 128 + (((lane >> 3) ^ l7) << 4);
        uint32_t o_sp = g * 256 + ((t ^ ((g & 1) << 2)) << 4);
        uint32_t a_spl = sm + SM_WUK + kq * 8192 + nh * 2048 + o_sp;
        uint32_t a_spr = smp + SM_SPR + warp * 2048 + o_sp;
        const int keyp = (lane & 16) + ((lane & 2) ? 8 + ((((lane >> 1) & 6) + (lane & 1)) ^ 4) : ((lane >> 1) & 6) + (lane & 1));
        uint32_t a_ct = sm + SM_CKV + kq * 16384 + keyp * 128 + (((4 * nh) ^ (keyp & 7)) << 4);
        uint32_t a_sr = sm + (lane >> 4) * 2048 + warp * 256 + (((lane & 15) ^ (nh << 2)) << 4);
        uint32_t o_pw = SM_P + (8 * r + warp) * 256 + (((lane >> 1) ^ warp) << 4) + (lane & 1) * 8;
        uint32_t a_pr = sm + SM_P + (lane & 15) * 256 + (((lane >> 4) ^ l7) << 4);
        uint2* p_stw = S->st + ((16 * pp + 8 * r + warp) * 32 + h) * 4 + lane;
        uint4* p_e3w = S->e3 + ((((16 * pp + g) * 2 + r) * 8 + warp) * 32 + h) * 4 + t;
        const uint4* p_e3r = S->e3 + ((h * 2 + r) * 8 + warp) * 128 + lane;
        const uint2* p_str = S->st + (h * 32 + lane) * 4;
        const int krow = l7 + 8 * (lane >> 4), csel = (lane >> 3) & 1;
        uint32_t a_w1 = sm + SM_W1 + (80 * kq + krow) * 64 + (((2 * nh + csel) ^ (l7 >> 1)) << 4);
        uint32_t a_wuv = sm + SM_WUV + (128 * (warp >> 2) + krow) * 128 + (((2 * (warp & 3) + csel) ^ l7) << 4);
        uint32_t a_vf3w = sm + SM_VF3 + t * 144 + warp * 16 + (lane >> 2) * 2;
        uint32_t a_vf3r = sm + SM_VF3 + (g & 1) * 576 + t * 144 + (warp >> 2) * 64;
        uint32_t a_fin[5];
#pragma unroll
        for (int i = 0; i < 5; i++) {
            const int N = 10 * (warp & 3) + 2 * i + csel;
            a_fin[i] = sm + (warp >> 2) * 10240 + (N >> 3) * 2048 + krow * 128 + (((N & 7) ^ l7) << 4);
            PIN(a_fin[i]);
        }
        uint32_t b_xc = (((warp >> 1) & 1) == r ? mapa(sm, r) : smp), b_xh = (nh == r ? mapa(sm, r) : smp);
        uint32_t a_xc = b_xc + SM_XC + ((warp & 1) * 16 + (t & 1) * 8 + g) * 16 + (2 * r + (warp >> 2)) * 4;
        uint32_t a_xh = b_xh + SM_XH + ((t & 1) * 8 + g) * 32 + (4 * r + kq) * 4;
        unsigned* p_e4w = reinterpret_cast<unsigned*>(S->e4) + ((10 * warp + t) * NCTA + b) * 8 + g;
        PIN(a_wuk); PINL(p_e2w); PINL(p_e2r); PIN(a_s); PIN(a_spl); PIN(a_spr); PIN(a_ct); PIN(a_sr); PIN(o_pw); PIN(a_pr);
        PINL(p_stw); PINL(p_e3w); PINL(p_e3r); PINL(p_str); PIN(a_w1); PIN(a_wuv); PIN(a_vf3w); PIN(a_vf3r); PIN(a_xc); PIN(a_xh); PINL(p_e4w);

        {
            float acc[8];
#pragma unroll
            for (int e = 0; e < 8; e++) acc[e] = 0.f;
#pragma unroll
            for (int i = 0; i < 10; i++) fma8(acc, (i & 1) ? bf_hi(xw[i >> 1]) : bf_lo(xw[i >> 1]), wv[i]);
            const bool up = lane >= 16;
            float k4[4];
#pragma unroll
            for (int e = 0; e < 4; e++) k4[e] = (up ? acc[4 + e] : acc[e]) + shfl_x(up ? acc[e] : acc[4 + e], 16);
            sts128(sm + SM_RED + warp * 512 + (tid & 15) * 32 + (lane & 16), k4[0], k4[1], k4[2], k4[3]);
        }
        STAMP(0);
        bar_sync(1, 320);
        const unsigned tag = lds32(sm + SM_G + 4);
        if (tid < 128) {
            float rv[8];
#pragma unroll
            for (int w = 0; w < 8; w++) rv[w] = __uint_as_float(lds32(sm + SM_RED + w * 512 + tid * 4));
            const float s = ((rv[0] + rv[1]) + (rv[2] + rv[3])) + ((rv[4] + rv[5]) + (rv[6] + rv[7]));
            unsigned* p1 = &S->e1[4 * h * 128 + tid];
            st_pub1(p1 + j * 128, tagf(s, tag));
            unsigned p[4];
            int it = 0;
#pragma unroll 1
            do {
#pragma unroll
                for (int s4 = 0; s4 < 4; s4++) p[s4] = ld_poll1(p1 + s4 * 128);
            } while ((((p[0] ^ tag) | (p[1] ^ tag) | (p[2] ^ tag) | (p[3] ^ tag)) & 1u) && ++it < SPIN_MAX);
            const float q = (untagf(p[0]) + untagf(p[1])) + (untagf(p[2]) + untagf(p[3]));
            sts16(sm + SM_VF1 + ((tid >> 1) & 3) * 80 + (tid >> 4) * 8 + ((tid >> 3) & 1) * 4 + (tid & 1) * 2, pack_bf16(q, 0.f));
        }
        STAMP(1);
        bar_sync(2, 288);
        {
            uint4 qf[4];
#pragma unroll
            for (int i = 0; i < 4; i++) qf[i] = lds128(sm + SM_VF1 + t * 80 + i * 16);
            mbar_wait(sm + SM_BAR + 8 * (B_WUK + kq));
            STAMP_T(224, 20);
            uint32_t a[8][4];
#pragma unroll
            for (int s = 0; s < 8; s++) ldsm4((a_wuk ^ ((s & 3) << 5)) + (s >> 2) * 4096, a[s]);
            float c[4][4];
#pragma unroll
            for (int i = 0; i < 4; i++) {
                c[i][0] = c[i][1] = c[i][2] = c[i][3] = 0.f;
                mma4(c[i], a[2 * i], qf[i].x, qf[i].y);
            }
#pragma unroll
            for (int i = 0; i < 4; i++) mma4(c[i], a[2 * i + 1], qf[i].z, qf[i].w);
            const float sc = 0.08838834764831845f * 1.4426950408889634f;
            const float lo = ((c[0][0] + c[1][0]) + (c[2][0] + c[3][0])) * sc;
            const float hi = ((c[0][2] + c[1][2]) + (c[2][2] + c[3][2])) * sc;
            const uint32_t lob = (lo != lo) ? 0x7FFEu : (((__float_as_uint(lo) + 0x10000u) >> 16) & 0xFFFEu);
            if (t == 0) st_pub1(p_e2w, (pack_bf16(0.f, hi) & 0xFFFF0000u) | lob | tag);
        }
        STAMP_T(224, 2);
        {
            uint32_t qa[4][4];
            asm volatile("barrier.cluster.wait.aligned;" ::: "memory");
            mbar_wait(sm + SM_BAR + 8 * (B_CKV + QGATE));
            STAMP(19);
            {
                int it = 0;
                const unsigned ft = tag - 1u;
                while (true) {
                    uint4 v[4];
#pragma unroll
                    for (int s = 0; s < 4; s++) v[s] = ld_poll4(p_e2r + s * 32);
                    unsigned ok = 1u;
#pragma unroll
                    for (int s = 0; s < 4; s++) {
                        ok &= (v[s].x ^ ft) & (v[s].y ^ ft) & (v[s].z ^ ft) & (v[s].w ^ ft);
                        qa[s][0] = v[s].x & ~1u; qa[s][1] = v[s].y & ~1u; qa[s][2] = v[s].z & ~1u; qa[s][3] = v[s].w & ~1u;
                    }
                    if (ok || ++it >= SPIN_MAX) break;
                    __nanosleep(BACKOFF);
                }
            }
            __syncwarp();
            STAMP(3);
            mbar_wait(sm + SM_BAR + 8 * (B_CKV + kq));
            STAMP_T(224, 4);
            {
                uint32_t bf[8][2][4];
#pragma unroll
                for (int n = 0; n < 8; n++) ldsm4((a_s ^ ((n & 1) * 0x240)) + n * 1024, bf[n][0]);
#pragma unroll
                for (int n = 0; n < 8; n++) ldsm4((a_s ^ ((n & 1) * 0x240) ^ 64) + n * 1024, bf[n][1]);
                float s[8][4];
#pragma unroll
                for (int n = 0; n < 8; n++) {
                    s[n][0] = s[n][1] = s[n][2] = s[n][3] = 0.f;
                    mma4(s[n], qa[0], bf[n][0][0], bf[n][0][1]);
                }
#pragma unroll
                for (int n = 0; n < 8; n++) mma4(s[n], qa[1], bf[n][0][2], bf[n][0][3]);
#pragma unroll
                for (int n = 0; n < 8; n++) mma4(s[n], qa[2], bf[n][1][0], bf[n][1][1]);
#pragma unroll
                for (int n = 0; n < 8; n++) mma4(s[n], qa[3], bf[n][1][2], bf[n][1][3]);
#pragma unroll
                for (int n = 0; n < 8; n++)
                    st_async2((a_spr ^ ((n >> 1) << 6)) + (n & 1) * 8, __float_as_uint(s[n][2]), __float_as_uint(s[n][3]), smp + SM_BAR + 8 * B_SP);
#pragma unroll
                for (int n = 0; n < 8; n++) sts64((a_spl ^ ((n >> 1) << 6)) + (n & 1) * 8, __float_as_uint(s[n][0]), __float_as_uint(s[n][1]));
            }
            uint32_t ct[4][4][4];
#pragma unroll
            for (int n = 0; n < 4; n++)
#pragma unroll
                for (int kb = 0; kb < 4; kb++) ldsm4t((a_ct ^ (n << 4)) + kb * 4096, ct[n][kb]);
            bar_sync(3, 256);
            STAMP(5);
            mbar_wait(sm + SM_BAR + 8 * B_SP);
            STAMP(6);
            {
                uint4 u[4], v[4];
#pragma unroll
                for (int q = 0; q < 4; q++) { u[q] = lds128(a_sr + SM_WUK + q * 8192); v[q] = lds128(a_sr + SM_SPR + q * 4096); }
#define SUM8(f) (((__uint_as_float(u[0].f) + __uint_as_float(u[1].f)) + (__uint_as_float(u[2].f) + __uint_as_float(u[3].f))) + \
                 ((__uint_as_float(v[0].f) + __uint_as_float(v[1].f)) + (__uint_as_float(v[2].f) + __uint_as_float(v[3].f))))
                const float s0 = SUM8(x), s1 = SUM8(y), s2 = SUM8(z), s3 = SUM8(w);
#undef SUM8
                const float m = warp_max(fmaxf(fmaxf(s0, s1), fmaxf(s2, s3)));
                const uint32_t p01 = pack_bf16(ex2(s0 - m), ex2(s1 - m));
                const uint32_t p23 = pack_bf16(ex2(s2 - m), ex2(s3 - m));
                st_async2(smp + o_pw, p01, p23, smp + SM_BAR + 8 * B_P);
                sts64(sm + o_pw, p01, p23);
                bar_sync(3, 256);
                float l = (bf_lo(p01) + bf_hi(p01)) + (bf_lo(p23) + bf_hi(p23));
#pragma unroll
                for (int d = 1; d < 32; d <<= 1) l += shfl_x(l, d);
                if (lane < 4) st_pub64(p_stw, tagf(l, tag), __float_as_uint(m));
            }
            mbar_wait(sm + SM_BAR + 8 * B_P);
            STAMP(7);
            {
                uint32_t pa[8][4];
#pragma unroll
                for (int s = 0; s < 8; s++) ldsm4(a_pr ^ (s << 5), pa[s]);
                float o[2][4][4];
#pragma unroll
                for (int n = 0; n < 4; n++)
#pragma unroll
                    for (int e = 0; e < 4; e++) o[0][n][e] = o[1][n][e] = 0.f;
#pragma unroll
                for (int i = 0; i < 4; i++) {
#pragma unroll
                    for (int n = 0; n < 4; n++) mma4(o[0][n], pa[2 * i], ct[n][i][0], ct[n][i][1]);
#pragma unroll
                    for (int n = 0; n < 4; n++) mma4(o[1][n], pa[2 * i + 1], ct[n][i][2], ct[n][i][3]);
                }
                uint32_t w0[4], w1[4];
#pragma unroll
                for (int n = 0; n < 4; n++) {
                    w0[n] = pack_bf16(o[0][n][0] + o[1][n][0], o[0][n][1] + o[1][n][1]);
                    w1[n] = pack_bf16(o[0][n][2] + o[1][n][2], o[0][n][3] + o[1][n][3]);
                }
                st_pub2x64(p_e3w, tagw(w0[0], tag), w0[1], tagw(w0[2], tag), w0[3]);
                st_pub2x64(p_e3w + 8 * 2 * 8 * 32 * 4, tagw(w1[0], tag), w1[1], tagw(w1[2], tag), w1[3]);
            }
        }
        STAMP(8);
        if (ffn) {
            const uint32_t xa = sm + SM_XS + 160 * kq + 4 * t;
            uint32_t xb[5][2];
#pragma unroll
            for (int s = 0; s < 5; s++) { xb[s][0] = lds32(xa + s * 32); xb[s][1] = lds32(xa + s * 32 + 16); }
            mbar_wait(sm + SM_BAR + 8 * (B_W1 + (warp >> 2)));
            uint32_t a[5][4];
#pragma unroll
            for (int s = 0; s < 5; s++) ldsm4t(a_w1 + s * 1024, a[s]);
            float c0[4] = {0.f, 0.f, 0.f, 0.f}, c1[4] = {0.f, 0.f, 0.f, 0.f};
#pragma unroll
            for (int s = 0; s < 5; s++) mma4((s & 1) ? c1 : c0, a[s], xb[s][0], xb[s][1]);
            if (t < 2) st_async1(a_xh, t ? c0[2] + c1[2] : c0[0] + c1[0], b_xh + SM_BAR + 8 * B_XH);
        }
        STAMP(9);
        {
            uint4 v[4];
            uint2 st;
            int it = 0;
            while (true) {
                st = ld_poll64(p_str);
#pragma unroll
                for (int i = 0; i < 4; i++) v[i] = ld_poll2x64(p_e3r + i * 32);
                unsigned bad = st.x ^ tag;
#pragma unroll
                for (int i = 0; i < 4; i++) bad |= (v[i].x ^ tag) | (v[i].z ^ tag);
                if (!(bad & 1u) || ++it >= SPIN_MAX) break;
                __nanosleep(BACKOFF);
            }
            __syncwarp();
            STAMP(10);
            const float M = warp_max(__uint_as_float(st.y));
            const float f = ex2(__uint_as_float(st.y) - M);
            float L = f * untagf(st.x);
            float acc[8];
#pragma unroll
            for (int e = 0; e < 8; e++) acc[e] = 0.f;
#pragma unroll
            for (int i = 0; i < 4; i++) {
                v[i].x &= ~1u; v[i].z &= ~1u;
                fma8(acc, __shfl_sync(0xffffffffu, f, 8 * i + g), v[i]);
            }
#pragma unroll
            for (int d = 1; d < 32; d <<= 1) L += shfl_x(L, d);
            const bool b4 = lane & 16, b3 = lane & 8, b2 = lane & 4;
            float k4[4], k2[2];
#pragma unroll
            for (int e = 0; e < 4; e++) k4[e] = (b4 ? acc[4 + e] : acc[e]) + shfl_x(b4 ? acc[e] : acc[4 + e], 16);
#pragma unroll
            for (int e = 0; e < 2; e++) k2[e] = (b3 ? k4[2 + e] : k4[e]) + shfl_x(b3 ? k4[e] : k4[2 + e], 8);
            const float s = __fdividef((b2 ? k2[1] : k2[0]) + shfl_x(b2 ? k2[0] : k2[1], 4), L);
            const uint32_t hi = pack_bf16(s, 0.f);
            sts16(a_vf3w, hi);
            sts16(a_vf3w + 576, pack_bf16(s - bf_lo(hi), 0.f));
        }
        {
            uint32_t a[8][4];
#pragma unroll
            for (int i = 0; i < 2; i++) {
                mbar_wait(sm + SM_BAR + 8 * (B_WUV + 2 * (warp >> 2) + i));
#pragma unroll
                for (int s = 0; s < 4; s++) ldsm4t(a_wuv + (4 * i + s) * 2048, a[4 * i + s]);
            }
            bar_sync(3, 256);
            STAMP(11);
            uint4 bv[4];
#pragma unroll
            for (int i = 0; i < 4; i++) bv[i] = lds128(a_vf3r + i * 16);
            float c[4][4];
#pragma unroll
            for (int i = 0; i < 4; i++) {
                c[i][0] = c[i][1] = c[i][2] = c[i][3] = 0.f;
                mma4(c[i], a[2 * i], bv[i].x, bv[i].y);
            }
#pragma unroll
            for (int i = 0; i < 4; i++) mma4(c[i], a[2 * i + 1], bv[i].z, bv[i].w);
            float e0[4];
#pragma unroll
            for (int i = 0; i < 4; i++) e0[i] = (t & 1) ? c[i][2] + c[i][3] : c[i][0] + c[i][1];
            if (t < 2) st_async1(a_xc, (e0[0] + e0[1]) + (e0[2] + e0[3]), b_xc + SM_BAR + 8 * B_XC);
        }
        STAMP(12);
        {
            float c[5][4];
#pragma unroll
            for (int i = 0; i < 5; i++) c[i][0] = c[i][1] = c[i][2] = c[i][3] = 0.f;
            const int half = warp >> 2;
            const float gt = __uint_as_float(lds32(sm + SM_G));
            if (ffn) {
                mbar_wait(sm + SM_BAR + 8 * B_XH);
                const uint4 u = lds128(sm + SM_XH + (lane & 15) * 32), v = lds128(sm + SM_XH + (lane & 15) * 32 + 16);
                float hv = ((__uint_as_float(u.x) + __uint_as_float(u.y)) + (__uint_as_float(u.z) + __uint_as_float(u.w))) +
                           ((__uint_as_float(v.x) + __uint_as_float(v.y)) + (__uint_as_float(v.z) + __uint_as_float(v.w)));
                hv = bf_lo(pack_bf16(hv, 0.f));
                hv = __fdividef(hv, 1.f + __expf(-hv)) * (1.f - gt);
                const uint32_t w = pack_bf16(hv, shfl_x(hv, 1));
                const uint32_t b0 = __shfl_sync(0xffffffffu, w, 2 * t), b1 = __shfl_sync(0xffffffffu, w, 8 + 2 * t);
                mbar_wait(sm + SM_BAR + 8 * (B_W2 + half));
                uint32_t a[5][4];
#pragma unroll
                for (int i = 0; i < 5; i++) ldsm4t(a_fin[i] + SM_W2, a[i]);
#pragma unroll
                for (int i = 0; i < 5; i++) mma4(c[i], a[i], b0, b1);
            }
            mbar_wait(sm + SM_BAR + 8 * B_XC);
            STAMP(13);
            const uint4 u = lds128(sm + SM_XC + lane * 16);
            const float cv = ((__uint_as_float(u.x) + __uint_as_float(u.y)) + (__uint_as_float(u.z) + __uint_as_float(u.w))) * gt;
            const uint32_t w = pack_bf16(cv, shfl_x(cv, 1));
            uint32_t bb[4];
#pragma unroll
            for (int q = 0; q < 4; q++) bb[q] = __shfl_sync(0xffffffffu, w, 8 * q + 2 * t);
#pragma unroll
            for (int s = 0; s < 2; s++) {
                mbar_wait(sm + SM_BAR + 8 * (B_WO + 2 * s + half));
                uint32_t a[5][4];
#pragma unroll
                for (int i = 0; i < 5; i++) ldsm4t(a_fin[i] + SM_WO + s * 20480, a[i]);
#pragma unroll
                for (int i = 0; i < 5; i++) mma4(c[i], a[i], bb[2 * s], bb[2 * s + 1]);
            }
            STAMP_T(224, 14);
            const bool t0 = t & 1, t1 = t & 2;
            const float v0 = t1 ? (t0 ? c[1][2] : c[1][0]) : (t0 ? c[0][2] : c[0][0]);
            const float v1 = t1 ? (t0 ? c[3][2] : c[3][0]) : (t0 ? c[2][2] : c[2][0]);
            const float v2 = t0 ? c[4][2] : c[4][0];
            st_pub1(p_e4w, tagf(v0, tag));
            st_pub1(p_e4w + 4 * NCTA * 8, tagf(v1, tag));
            if (!t1) st_pub1(p_e4w + 8 * NCTA * 8, tagf(v2, tag));
        }
        STAMP_T(224, 15);
    } else if (warp == 8) {
        const unsigned t0 = gtimer();
        const uint32_t bar = sm + SM_BAR + 8 * lane;
        asm volatile("mbarrier.init.shared::cta.b64 [%0], 1;" :: "r"(bar) : "memory");
        if (lane >= B_SP) {
            const uint32_t tx = lane == B_SP ? 16384u : lane == B_P ? 2048u : 512u;
            asm volatile("mbarrier.arrive.expect_tx.shared::cta.b64 _, [%0], %1;" :: "r"(bar), "r"(tx) : "memory");
        }
        asm volatile("fence.mbarrier_init.release.cluster;" ::: "memory");
        asm volatile("barrier.cluster.arrive.relaxed.aligned;" ::: "memory");
        bar_arrive(1, 320);
        if (lane < 6) asm volatile("prefetch.tensormap [%0];" :: "l"(&P.m[lane]) : "memory");
        {
            int map, c0 = 0, c1, c2;
            uint32_t dst, bytes, due;
            const int k = lane;
            constexpr int DF = DT_NS * 135 / 128;
            if (k < B_CKV)      { map = 0; c1 = 128 * j + 32 * k;            c2 = 2 * h;              dst = SM_WUK + k * 8192;            bytes = 8192;  due = k * DT_NS; }
            else if (k < B_W1)  { map = 1; c1 = 128 * h;                     c2 = 4 * r + k - B_CKV;  dst = SM_CKV + (k - B_CKV) * 16384; bytes = 16384; due = k * DT_NS; }
            else if (k < B_WUV) { map = 2; c1 = 320 * r + 160 * (k - B_W1);  c2 = h; c0 = 32 * pp;    dst = SM_W1 + (k - B_W1) * 10240;   bytes = ffn ? 10240 : 0; due = 8 * DT_NS + (k - B_W1) * DF; }
            else if (k < B_W2)  { map = 3; c1 = 256 * r + 64 * (k - B_WUV);  c2 = 2 * h + pp;         dst = SM_WUV + (k - B_WUV) * 8192;  bytes = 8192;  due = (k - 2) * DT_NS + 2 * DF; }
            else if (k < B_WO)  { map = 4; c1 = 16 * b;                      c2 = 5 * (k - B_W2);     dst = SM_W2 + (k - B_W2) * 10240;   bytes = ffn ? 10240 : 0; due = 12 * DT_NS + (k - 12) * DF; }
            else                { map = 5; c1 = 32 * b + 16 * ((k - B_WO) >> 1); c2 = 5 * (k & 1);    dst = SM_WO + (k - B_WO) * 10240;   bytes = k < B_SP ? 10240 : 0;
                                  due = 12 * DT_NS + 4 * DF + (k - B_WO) * (DT_NS * 5 / 4); }
            due += T0_NS;
            bool pending = bytes != 0;
            if (pending) asm volatile("mbarrier.arrive.expect_tx.shared::cta.b64 _, [%0], %1;" :: "r"(bar), "r"(bytes) : "memory");
            STAMP_T(256, 21);
            while (__any_sync(0xffffffffu, pending)) {
                const unsigned now = gtimer() - t0;
                if (pending && now >= due) {
                    asm volatile("cp.async.bulk.tensor.3d.shared::cluster.global.mbarrier::complete_tx::bytes [%0], [%1, {%3,%4,%5}], [%2];"
                                 :: "r"(sm + dst), "l"(&P.m[map]), "r"(bar), "r"(c0), "r"(c1), "r"(c2) : "memory");
                    pending = false;
                }
            }
        }
        STAMP_T(256, 22);
        if (b < 80) {
            const uint4* p = S->e4 + b * NCTA * 2 + lane;
            mbar_wait(sm + SM_BAR + 8 * B_XC);
            const unsigned tag = lds32(sm + SM_G + 4);
            const unsigned ft = tag - 1u;
            mbar_wait(sm + SM_BAR + 8 * (B_WO + 3));
            STAMP_T(256, 16);
            uint4 v[8];
            bool bad[8];
#pragma unroll
            for (int i = 0; i < 8; i++) bad[i] = true;
            int it = 0;
            bool any;
#pragma unroll 1
            do {
#pragma unroll
                for (int i = 0; i < 8; i++) if (bad[i]) v[i] = ld_poll4(p + i * 32);
                any = false;
#pragma unroll
                for (int i = 0; i < 8; i++) { bad[i] = !((v[i].x ^ ft) & (v[i].y ^ ft) & (v[i].z ^ ft) & (v[i].w ^ ft) & 1u); any |= bad[i]; }
            } while (any && ++it < SPIN_MAX);
            __syncwarp();
#define SUM8(f) (((untagf(v[0].f) + untagf(v[1].f)) + (untagf(v[2].f) + untagf(v[3].f))) + ((untagf(v[4].f) + untagf(v[5].f)) + (untagf(v[6].f) + untagf(v[7].f))))
            const float s0 = SUM8(x), s1 = SUM8(y), s2 = SUM8(z), s3 = SUM8(w);
#undef SUM8
            const bool b4 = lane & 16, b3 = lane & 8;
            const float k0 = (b4 ? s2 : s0) + shfl_x(b4 ? s0 : s2, 16);
            const float k1 = (b4 ? s3 : s1) + shfl_x(b4 ? s1 : s3, 16);
            float s = (b3 ? k1 : k0) + shfl_x(b3 ? k0 : k1, 8);
            s += shfl_x(s, 4);
            s += shfl_x(s, 2);
            if (!(lane & 6)) P.out[b * 8 + (lane & 1) * 4 + (lane >> 3)] = __float2bfloat16(s);
            if (b == 0 && lane == 0) st_pub1(&S->epoch, tag);
            STAMP_T(256, 17);
        }
    } else {
        const unsigned old = ld_poll1(&S->epoch) & 1u;
        uint32_t xv[10], gw[10];
#pragma unroll
        for (int i = 0; i < 10; i++) {
            xv[i] = ldg32(P.x + (i * 32 + lane) * 2);
            gw[i] = ldg32(P.gate + (i * 32 + lane) * 2);
        }
        asm volatile("barrier.cluster.arrive.relaxed.aligned;" ::: "memory");
        st_pub4(&S->e1[b * 128 + lane * 4], old, old, old, old);
        {
            unsigned* p2 = reinterpret_cast<unsigned*>(S->e2) +
                           (((((h >> 4) * 2 + pp) * 16 + 8 * r + (lane >> 2)) * 32) + (h & 7) * 4 + (lane & 3)) * 4 + (((h >> 3) & 1) ^ pp);
            st_pub1(p2, old);
            st_pub1(p2 + 2, old);
        }
        if (lane == 0) sts32(sm + SM_G + 4, old ^ 1u);
        bar_arrive(1, 320);
        STAMP_T(288, 18);
#pragma unroll
        for (int i = 0; i < 5; i++) st_pub4(&S->e4[((i * 16 + (lane >> 1)) * NCTA + b) * 2 + (lane & 1)], old, old, old, old);
        float z = 0.f;
#pragma unroll
        for (int i = 0; i < 10; i++) {
            if ((i >= 5) == (r != 0)) sts32(sm + SM_XS + ((i % 5) * 32 + lane) * 4, xv[i]);
            z = fmaf(bf_lo(xv[i]), bf_lo(gw[i]), z);
            z = fmaf(bf_hi(xv[i]), bf_hi(gw[i]), z);
        }
#pragma unroll
        for (int d = 1; d < 32; d <<= 1) z += shfl_x(z, d);
        if (lane == 0) sts32(sm + SM_G, __float_as_uint(__fdividef(1.f, 1.f + __expf(-z))));
        bar_arrive(2, 288);
        STAMP_T(288, 23);
    }
}

typedef CUresult (*EncodeFn)(CUtensorMap*, CUtensorMapDataType, cuuint32_t, void*, const cuuint64_t*, const cuuint64_t*,
                             const cuuint32_t*, const cuuint32_t*, CUtensorMapInterleave, CUtensorMapSwizzle,
                             CUtensorMapL2promotion, CUtensorMapFloatOOBfill);

void make_map(EncodeFn enc, CUtensorMap* m, const void* base, int rows, int cols, int box_cols, int box_rows, int box_blks) {
    cuuint64_t gd[3] = {64, (cuuint64_t)rows, (cuuint64_t)(cols / 64)};
    cuuint64_t gs[2] = {(cuuint64_t)cols * 2, 128};
    cuuint32_t bd[3] = {(cuuint32_t)box_cols, (cuuint32_t)box_rows, (cuuint32_t)box_blks};
    cuuint32_t es[3] = {1, 1, 1};
    enc(m, CU_TENSOR_MAP_DATA_TYPE_BFLOAT16, 3, const_cast<void*>(base), gd, gs, bd, es, CU_TENSOR_MAP_INTERLEAVE_NONE,
        box_cols == 64 ? CU_TENSOR_MAP_SWIZZLE_128B : CU_TENSOR_MAP_SWIZZLE_64B,
        box_cols == 64 ? CU_TENSOR_MAP_L2_PROMOTION_NONE : CU_TENSOR_MAP_L2_PROMOTION_L2_128B, CU_TENSOR_MAP_FLOAT_OOB_FILL_NONE);
}

}

extern "C" void kernel_launch(void* const* d_in, const int* in_sizes, int n_in, void* d_out, int out_size) {
    (void)in_sizes; (void)n_in; (void)out_size;
    constexpr int smem_bytes = SMEM_BYTES;
    static EncodeFn enc = nullptr;
    static Scratch* scratch = nullptr;
    if (!enc) {
        void* fn = nullptr;
        cudaDriverEntryPointQueryResult st;
        cudaGetDriverEntryPoint("cuTensorMapEncodeTiled", &fn, cudaEnableDefault, &st);
        enc = (EncodeFn)fn;
        cudaFuncSetAttribute(fused_kernel, cudaFuncAttributeMaxDynamicSharedMemorySize, smem_bytes);
        cudaGetSymbolAddress((void**)&scratch, g_s);
    }
    Params p;
    make_map(enc, &p.m[0], d_in[3], 512, 4096, 64, 32, 2);
    make_map(enc, &p.m[1], d_in[1], 4096, 512, 64, 128, 1);
    make_map(enc, &p.m[2], d_in[7], 640, 1728, 32, 160, 1);
    make_map(enc, &p.m[3], d_in[4], 512, 4096, 64, 64, 1);
    make_map(enc, &p.m[4], d_in[8], 1728, 640, 64, 16, 5);
    make_map(enc, &p.m[5], d_in[5], 4096, 640, 64, 16, 5);
    p.x = (const __nv_bfloat16*)d_in[0];
    p.wq = (const __nv_bfloat16*)d_in[2];
    p.gate = (const __nv_bfloat16*)d_in[9];
    p.out = (__nv_bfloat16*)d_out;
    p.s = scratch;
    fused_kernel<<<NCTA, NTHREADS, smem_bytes>>>(p);
}
```

```cpp
#include <cuda_runtime.h>
#include <cuda.h>
#include <cuda_bf16.h>
#include <stdint.h>

namespace {

constexpr int NCTA = 128;
constexpr int NTHREADS = 320;
constexpr int SPIN_MAX = 1 << 18;

constexpr int SM_WUK = 0;
constexpr int SM_CKV = SM_WUK + 32768;
constexpr int SM_WUV = SM_CKV + 65536;
constexpr int SM_W1  = SM_WUV + 32768;
constexpr int SM_W2  = SM_W1 + 20480;
constexpr int SM_WO  = SM_W2 + 20480;
constexpr int SM_SPR = SM_WO + 40960;
constexpr int SM_RED = SM_SPR;
constexpr int SM_QS  = SM_WUK;
constexpr int SM_SPL = SM_WUK + 8192;
constexpr int SM_P   = SM_WUK + 16384;
constexpr int SM_VF3 = SM_WUK + 20480;
constexpr int SM_VF1 = SM_SPR + 8192;
constexpr int SM_XS  = SM_VF1 + 320;
constexpr int SM_XC  = SM_XS + 640;
constexpr int SM_XH  = SM_XC + 512;
constexpr int SM_G   = SM_XH + 512;
constexpr int SM_BAR = SM_G + 32;
constexpr int SM_END = SM_BAR + 32 * 8;
constexpr int SMEM_BYTES = SM_END;
static_assert(SMEM_BYTES <= 232448 - 256, "smem");

constexpr int B_WUK = 0, B_CKV = 4, B_W1 = 8, B_WUV = 10, B_W2 = 14, B_WO = 16, B_SP = 20, B_XC = 21, B_XH = 22, NBAR = 23;

struct Scratch {
    uint4    e3[32 * 2 * 8 * 32 * 4];
    uint4    e4[80 * NCTA * 2];
    unsigned e1[NCTA * 128];
    uint4    e2[2 * 2 * 16 * 32];
    uint2    st[32 * 32 * 4];
    unsigned epoch;
};
__device__ __align__(1024) Scratch g_s;

struct Params {
    const __nv_bfloat16* wq;
    const __nv_bfloat16* x;
    Scratch* s;
    const __nv_bfloat16* gate;
    __nv_bfloat16* out;
    alignas(64) CUtensorMap m[6];
};

#define STAMP(i)
#define STAMP_T(t, i)

__device__ __forceinline__ unsigned clock32() { unsigned c; asm volatile("mov.u32 %0, %%clock;" : "=r"(c) :: "memory"); return c; }
__device__ __forceinline__ unsigned gtimer() { unsigned c; asm volatile("mov.u32 %0, %%globaltimer_lo;" : "=r"(c) :: "memory"); return c; }

__device__ __forceinline__ uint4 ldg_stream(const void* p) {
    uint4 v;
    asm volatile("ld.global.nc.L1::no_allocate.v4.u32 {%0,%1,%2,%3}, [%4];"
                 : "=r"(v.x), "=r"(v.y), "=r"(v.z), "=r"(v.w) : "l"(p));
    return v;
}
__device__ __forceinline__ uint4 ld_poll4(const void* p) {
    uint4 v;
    asm volatile("ld.relaxed.gpu.global.v4.u32 {%0,%1,%2,%3}, [%4];"
                 : "=r"(v.x), "=r"(v.y), "=r"(v.z), "=r"(v.w) : "l"(p) : "memory");
    return v;
}
__device__ __forceinline__ uint4 ld_poll2x64(const void* p) {
    uint4 v;
    asm volatile("{.reg .b64 a, b; ld.relaxed.gpu.global.v2.b64 {a, b}, [%4]; mov.b64 {%0,%1}, a; mov.b64 {%2,%3}, b;}"
                 : "=r"(v.x), "=r"(v.y), "=r"(v.z), "=r"(v.w) : "l"(p) : "memory");
    return v;
}
__device__ __forceinline__ uint2 ld_poll64(const void* p) {
    uint2 v;
    asm volatile("{.reg .b64 a; ld.relaxed.gpu.global.b64 a, [%2]; mov.b64 {%0,%1}, a;}" : "=r"(v.x), "=r"(v.y) : "l"(p) : "memory");
    return v;
}
__device__ __forceinline__ unsigned ld_poll1(const void* p) {
    unsigned v;
    asm volatile("ld.relaxed.gpu.global.u32 %0, [%1];" : "=r"(v) : "l"(p) : "memory");
    return v;
}
__device__ __forceinline__ void st_pub2x64(void* p, unsigned a, unsigned b, unsigned c, unsigned d) {
    asm volatile("{.reg .b64 x, y; mov.b64 x, {%1,%2}; mov.b64 y, {%3,%4}; st.relaxed.gpu.global.v2.b64 [%0], {x, y};}"
                 :: "l"(p), "r"(a), "r"(b), "r"(c), "r"(d) : "memory");
}
__device__ __forceinline__ void st_pub64(void* p, unsigned a, unsigned b) {
    asm volatile("{.reg .b64 x; mov.b64 x, {%1,%2}; st.relaxed.gpu.global.b64 [%0], x;}" :: "l"(p), "r"(a), "r"(b) : "memory");
}
__device__ __forceinline__ void st_pub1(void* p, unsigned a) {
    asm volatile("st.relaxed.gpu.global.u32 [%0], %1;" :: "l"(p), "r"(a) : "memory");
}
__device__ __forceinline__ unsigned tagw(unsigned w, unsigned tag) { return (w & ~1u) | tag; }
__device__ __forceinline__ unsigned tagf(float v, unsigned tag) { return (__float_as_uint(v) & ~1u) | tag; }
__device__ __forceinline__ float untagf(unsigned w) { return __uint_as_float(w & ~1u); }

__device__ __forceinline__ void mbar_wait(uint32_t bar) {
    uint32_t ok;
    int it = 0;
#pragma unroll 1
    do {
        asm volatile("{.reg .pred p; mbarrier.try_wait.parity.shared::cta.b64 p, [%1], 0; selp.u32 %0,1,0,p;}"
                     : "=r"(ok) : "r"(bar) : "memory");
    } while (!ok && ++it < SPIN_MAX);
}
__device__ __forceinline__ void bar_sync(int id, int n) { asm volatile("bar.sync %0, %1;" :: "r"(id), "r"(n) : "memory"); }
__device__ __forceinline__ void bar_arrive(int id, int n) { asm volatile("bar.arrive %0, %1;" :: "r"(id), "r"(n) : "memory"); }
__device__ __forceinline__ uint32_t mapa(uint32_t a, uint32_t rank) {
    uint32_t r;
    asm("mapa.shared::cluster.u32 %0, %1, %2;" : "=r"(r) : "r"(a), "r"(rank));
    return r;
}
__device__ __forceinline__ void st_async4(uint32_t a, float x, float y, float z, float w, uint32_t bar) {
    asm volatile("st.async.weak.shared::cluster.mbarrier::complete_tx::bytes.v4.f32 [%0], {%1,%2,%3,%4}, [%5];"
                 :: "r"(a), "f"(x), "f"(y), "f"(z), "f"(w), "r"(bar) : "memory");
}
__device__ __forceinline__ void st_async2(uint32_t a, uint32_t x, uint32_t y, uint32_t bar) {
    asm volatile("st.async.weak.shared::cluster.mbarrier::complete_tx::bytes.v2.b32 [%0], {%1,%2}, [%3];"
                 :: "r"(a), "r"(x), "r"(y), "r"(bar) : "memory");
}

__device__ __forceinline__ void ldsm4(uint32_t a, uint32_t (&r)[4]) {
    asm volatile("ldmatrix.sync.aligned.m8n8.x4.shared.b16 {%0,%1,%2,%3}, [%4];"
                 : "=r"(r[0]), "=r"(r[1]), "=r"(r[2]), "=r"(r[3]) : "r"(a) : "memory");
}
__device__ __forceinline__ void ldsm4t(uint32_t a, uint32_t (&r)[4]) {
    asm volatile("ldmatrix.sync.aligned.m8n8.x4.trans.shared.b16 {%0,%1,%2,%3}, [%4];"
                 : "=r"(r[0]), "=r"(r[1]), "=r"(r[2]), "=r"(r[3]) : "r"(a) : "memory");
}
__device__ __forceinline__ void mma(float (&c)[4], uint32_t a0, uint32_t a1, uint32_t a2, uint32_t a3, uint32_t b0, uint32_t b1) {
    asm("mma.sync.aligned.m16n8k16.row.col.f32.bf16.bf16.f32 {%0,%1,%2,%3}, {%4,%5,%6,%7}, {%8,%9}, {%0,%1,%2,%3};"
        : "+f"(c[0]), "+f"(c[1]), "+f"(c[2]), "+f"(c[3])
        : "r"(a0), "r"(a1), "r"(a2), "r"(a3), "r"(b0), "r"(b1));
}
__device__ __forceinline__ uint32_t pack_bf16(float lo, float hi) {
    uint32_t r;
    asm("cvt.rn.bf16x2.f32 %0, %1, %2;" : "=r"(r) : "f"(hi), "f"(lo));
    return r;
}
__device__ __forceinline__ float bf_lo(uint32_t w) { return __uint_as_float(w << 16); }
__device__ __forceinline__ float bf_hi(uint32_t w) { return __uint_as_float(w & 0xFFFF0000u); }
__device__ __forceinline__ float ex2(float x) { float y; asm("ex2.approx.ftz.f32 %0, %1;" : "=f"(y) : "f"(x)); return y; }
__device__ __forceinline__ uint4 lds128(uint32_t a) {
    uint4 v;
    asm volatile("ld.shared.v4.u32 {%0,%1,%2,%3}, [%4];" : "=r"(v.x), "=r"(v.y), "=r"(v.z), "=r"(v.w) : "r"(a) : "memory");
    return v;
}
__device__ __forceinline__ float2 lds64f(uint32_t a) {
    float2 v;
    asm volatile("ld.shared.v2.f32 {%0,%1}, [%2];" : "=f"(v.x), "=f"(v.y) : "r"(a) : "memory");
    return v;
}
__device__ __forceinline__ uint32_t lds32(uint32_t a) {
    uint32_t v;
    asm volatile("ld.shared.u32 %0, [%1];" : "=r"(v) : "r"(a) : "memory");
    return v;
}
__device__ __forceinline__ void sts128(uint32_t a, float x, float y, float z, float w) {
    asm volatile("st.shared.v4.f32 [%0], {%1,%2,%3,%4};" :: "r"(a), "f"(x), "f"(y), "f"(z), "f"(w) : "memory");
}
__device__ __forceinline__ void sts64(uint32_t a, uint32_t x, uint32_t y) {
    asm volatile("st.shared.v2.u32 [%0], {%1,%2};" :: "r"(a), "r"(x), "r"(y) : "memory");
}
__device__ __forceinline__ void sts32(uint32_t a, uint32_t x) {
    asm volatile("st.shared.u32 [%0], %1;" :: "r"(a), "r"(x) : "memory");
}
__device__ __forceinline__ void sts16(uint32_t a, uint32_t x) {
    asm volatile("st.shared.u16 [%0], %1;" :: "r"(a), "h"((unsigned short)x) : "memory");
}
__device__ __forceinline__ void fma8(float (&acc)[8], float s, const uint4& v) {
    acc[0] = fmaf(s, bf_lo(v.x), acc[0]); acc[1] = fmaf(s, bf_hi(v.x), acc[1]);
    acc[2] = fmaf(s, bf_lo(v.y), acc[2]); acc[3] = fmaf(s, bf_hi(v.y), acc[3]);
    acc[4] = fmaf(s, bf_lo(v.z), acc[4]); acc[5] = fmaf(s, bf_hi(v.z), acc[5]);
    acc[6] = fmaf(s, bf_lo(v.w), acc[6]); acc[7] = fmaf(s, bf_hi(v.w), acc[7]);
}
__device__ __forceinline__ float warp_max(float v) {
    int k = __float_as_int(v);
    k ^= (k >> 31) & 0x7FFFFFFF;
    asm("redux.sync.max.s32 %0, %0, 0xffffffff;" : "+r"(k));
    k ^= (k >> 31) & 0x7FFFFFFF;
    return __int_as_float(k);
}

__device__ __forceinline__ void st_async1(uint32_t a, float x, uint32_t bar) {
    asm volatile("st.async.weak.shared::cluster.mbarrier::complete_tx::bytes.f32 [%0], %1, [%2];" :: "r"(a), "f"(x), "r"(bar) : "memory");
}
__device__ __forceinline__ void st_pub4(void* p, unsigned a, unsigned b, unsigned c, unsigned d) {
    asm volatile("st.relaxed.gpu.global.v4.u32 [%0], {%1,%2,%3,%4};" :: "l"(p), "r"(a), "r"(b), "r"(c), "r"(d) : "memory");
}
__device__ __forceinline__ uint32_t ldg32(const void* p) {
    uint32_t v;
    asm volatile("ld.global.nc.u32 %0, [%1];" : "=r"(v) : "l"(p));
    return v;
}
__device__ __forceinline__ void mma4(float (&c)[4], const uint32_t (&a)[4], uint32_t b0, uint32_t b1) { mma(c, a[0], a[1], a[2], a[3], b0, b1); }
__device__ __forceinline__ float shfl_x(float v, int m) { return __shfl_xor_sync(0xffffffffu, v, m); }
__device__ __forceinline__ unsigned chk(unsigned acc, unsigned w, unsigned tag) {
    unsigned d;
    asm("lop3.b32 %0, %1, %2, %3, 0xF6;" : "=r"(d) : "r"(acc), "r"(w), "r"(tag));
    return d;
}
__device__ __forceinline__ unsigned chk4(unsigned acc, const uint4& v, unsigned tag) { return chk(chk(chk(chk(acc, v.x, tag), v.y, tag), v.z, tag), v.w, tag); }
__device__ __forceinline__ void sts128u(uint32_t a, uint32_t x, uint32_t y, uint32_t z, uint32_t w) {
    asm volatile("st.shared.v4.u32 [%0], {%1,%2,%3,%4};" :: "r"(a), "r"(x), "r"(y), "r"(z), "r"(w) : "memory");
}
#define PIN(x) asm volatile("" : "+r"(x))
#define PINL(x) asm volatile("" : "+l"(x))

#define T0_NS 1400
#define DT_NS 325
#define QGATE 1
#define BACKOFF 64

__global__ void __cluster_dims__(2, 1, 1) __launch_bounds__(NTHREADS, 1)
fused_kernel(const __grid_constant__ Params P)
{
    extern __shared__ __align__(1024) unsigned char smem_raw[];
    const int tid = threadIdx.x;
    const int b = blockIdx.x;
    const int h = b >> 2, j = b & 3;
    uint4 wv[10];
    uint32_t xw[5];
    if (tid < 256) {
        const int m0 = 160 * j + 10 * (tid >> 4);
        const __nv_bfloat16* wp = P.wq + (size_t)m0 * 4096 + h * 128 + (tid & 15) * 8;
#pragma unroll
        for (int i = 0; i < 10; i++) wv[i] = ldg_stream(wp + i * 4096);
#pragma unroll
        for (int i = 0; i < 5; i++) xw[i] = ldg32(P.x + m0 + 2 * i);
    }
    const int r = b & 1, pp = (b >> 1) & 1;
    const int warp = tid >> 5, lane = tid & 31;
    const uint32_t sm = (uint32_t)__cvta_generic_to_shared(smem_raw);
    const bool ffn = h < 27;
    Scratch* const S = P.s;

    if (warp < 8) {
        asm volatile("barrier.cluster.arrive.relaxed.aligned;" ::: "memory");
        const int g = lane >> 2, t = lane & 3, l7 = lane & 7;
        const int kq = warp >> 1, nh = warp & 1;
        const uint32_t smp = mapa(sm, r ^ 1);
        const int row1 = nh * 16 + 2 * l7 + ((lane >> 3) & 1);
        uint32_t a_wuk = sm + SM_WUK + kq * 8192 + row1 * 128 + (((lane >> 4) ^ (row1 & 7)) << 4);
        unsigned* p_e2w = reinterpret_cast<unsigned*>(S->e2) +
                          (((((h >> 4) * 2 + pp) * 16 + 8 * r + warp) * 32) + (h & 7) * 4 + (g & 3)) * 4 + ((h >> 3) & 1) + 2 * (g >> 2);
        const uint4* p_e2r = S->e2 + (pp * 2 + r) * 512 + tid;
        uint32_t a_s = sm + SM_CKV + (16 * warp + l7) * 128 + (((lane >> 3) ^ l7) << 4);
        uint32_t o_spw = warp * 1024 + ((lane ^ (nh << 2)) << 4);
        uint32_t a_ct = sm + SM_CKV + kq * 16384 + lane * 128 + (((4 * nh) ^ l7) << 4);
        uint32_t a_sr = sm + g * 1024 + ((warp ^ (g & 1)) << 6) + t * 16;
        uint2* p_stw = S->st + ((16 * pp + 8 * r + warp) * 32 + h) * 4 + lane;
        uint4* p_e3w = S->e3 + ((((16 * pp + g) * 2 + r) * 8 + warp) * 32 + h) * 4 + t;
        const uint4* p_e3r = S->e3 + ((h * 2 + r) * 8 + warp) * 128 + lane;
        const uint2* p_str = S->st + (h * 32 + lane) * 4;
        const int krow = l7 + 8 * (lane >> 4), csel = (lane >> 3) & 1;
        uint32_t a_w1 = sm + SM_W1 + (80 * kq + krow) * 64 + (((2 * nh + csel) ^ (l7 >> 1)) << 4);
        uint32_t a_wuv = sm + SM_WUV + (128 * (warp >> 2) + krow) * 128 + (((2 * (warp & 3) + csel) ^ l7) << 4);
        uint32_t a_vf3w = sm + SM_VF3 + t * 144 + warp * 16 + (lane >> 2) * 2;
        uint32_t a_vf3r = sm + SM_VF3 + (g & 1) * 576 + t * 144 + (warp >> 2) * 64;
        uint32_t a_fin[5];
#pragma unroll
        for (int i = 0; i < 5; i++) {
            const int N = 10 * (warp & 3) + 2 * i + csel;
            a_fin[i] = sm + (warp >> 2) * 10240 + (N >> 3) * 2048 + krow * 128 + (((N & 7) ^ l7) << 4);
            PIN(a_fin[i]);
        }
        uint32_t b_xc = (((warp >> 1) & 1) == r ? mapa(sm, r) : smp), b_xh = (nh == r ? mapa(sm, r) : smp);
        uint32_t a_xc = b_xc + SM_XC + ((warp & 1) * 16 + (t & 1) * 8 + g) * 16 + (2 * r + (warp >> 2)) * 4;
        uint32_t a_xh = b_xh + SM_XH + ((t & 1) * 8 + g) * 32 + (4 * r + kq) * 4;
        unsigned* p_e4w = reinterpret_cast<unsigned*>(S->e4) + ((10 * warp + t) * NCTA + b) * 8 + g;
        PIN(a_wuk); PINL(p_e2w); PINL(p_e2r); PIN(a_s); PIN(o_spw); PIN(a_ct); PIN(a_sr);
        PINL(p_stw); PINL(p_e3w); PINL(p_e3r); PINL(p_str); PIN(a_w1); PIN(a_wuv); PIN(a_vf3w); PIN(a_vf3r); PIN(a_xc); PIN(a_xh); PINL(p_e4w);

        {
            float acc[8];
#pragma unroll
            for (int e = 0; e < 8; e++) acc[e] = 0.f;
#pragma unroll
            for (int i = 0; i < 10; i++) fma8(acc, (i & 1) ? bf_hi(xw[i >> 1]) : bf_lo(xw[i >> 1]), wv[i]);
            const bool up = lane >= 16;
            float k4[4];
#pragma unroll
            for (int e = 0; e < 4; e++) k4[e] = (up ? acc[4 + e] : acc[e]) + shfl_x(up ? acc[e] : acc[4 + e], 16);
            sts128(sm + SM_RED + warp * 512 + (tid & 15) * 32 + (lane & 16), k4[0], k4[1], k4[2], k4[3]);
        }
        STAMP(0);
        bar_sync(1, 320);
        const unsigned tag = lds32(sm + SM_G + 4);
        if (tid < 128) {
            float rv[8];
#pragma unroll
            for (int w = 0; w < 8; w++) rv[w] = __uint_as_float(lds32(sm + SM_RED + w * 512 + tid * 4));
            const float s = ((rv[0] + rv[1]) + (rv[2] + rv[3])) + ((rv[4] + rv[5]) + (rv[6] + rv[7]));
            unsigned* p1 = &S->e1[4 * h * 128 + tid];
            st_pub1(p1 + j * 128, tagf(s, tag));
            unsigned p[4];
            int it = 0;
#pragma unroll 1
            do {
#pragma unroll
                for (int s4 = 0; s4 < 4; s4++) p[s4] = ld_poll1(p1 + s4 * 128);
            } while ((chk(chk(chk(p[0] ^ tag, p[1], tag), p[2], tag), p[3], tag) & 1u) && ++it < SPIN_MAX);
            const float q = (untagf(p[0]) + untagf(p[1])) + (untagf(p[2]) + untagf(p[3]));
            sts16(sm + SM_VF1 + ((tid >> 1) & 3) * 80 + (tid >> 4) * 8 + ((tid >> 3) & 1) * 4 + (tid & 1) * 2, pack_bf16(q, 0.f));
        }
        STAMP(1);
        bar_sync(2, 288);
        {
            uint4 qf[4];
#pragma unroll
            for (int i = 0; i < 4; i++) qf[i] = lds128(sm + SM_VF1 + t * 80 + i * 16);
            mbar_wait(sm + SM_BAR + 8 * (B_WUK + kq));
            STAMP_T(224, 20);
            uint32_t a[8][4];
#pragma unroll
            for (int s = 0; s < 8; s++) ldsm4((a_wuk ^ ((s & 3) << 5)) + (s >> 2) * 4096, a[s]);
            float c[4][4];
#pragma unroll
            for (int i = 0; i < 4; i++) {
                c[i][0] = c[i][1] = c[i][2] = c[i][3] = 0.f;
                mma4(c[i], a[2 * i], qf[i].x, qf[i].y);
            }
#pragma unroll
            for (int i = 0; i < 4; i++) mma4(c[i], a[2 * i + 1], qf[i].z, qf[i].w);
            const float sc = 0.08838834764831845f * 1.4426950408889634f;
            const float lo = ((c[0][0] + c[1][0]) + (c[2][0] + c[3][0])) * sc;
            const float hi = ((c[0][2] + c[1][2]) + (c[2][2] + c[3][2])) * sc;
            const uint32_t lob = (lo != lo) ? 0x7FFEu : (((__float_as_uint(lo) + 0x10000u) >> 16) & 0xFFFEu);
            if (t == 0) st_pub1(p_e2w, (pack_bf16(0.f, hi) & 0xFFFF0000u) | lob | tag);
        }
        STAMP_T(224, 2);
        {
            bar_sync(3, 256);
            asm volatile("barrier.cluster.wait.aligned;" ::: "memory");
            mbar_wait(sm + SM_BAR + 8 * (B_CKV + QGATE));
            STAMP(19);
            {
                uint4 v0, v1;
                int it = 0;
                while (true) {
                    v0 = ld_poll4(p_e2r);
                    v1 = ld_poll4(p_e2r + 256);
                    if (!(chk4(chk4(0u, v0, tag), v1, tag) & 1u) || ++it >= SPIN_MAX) break;
                    __nanosleep(BACKOFF);
                }
                sts128u(sm + SM_QS + tid * 16, v0.x & ~1u, v0.y & ~1u, v0.z & ~1u, v0.w & ~1u);
                sts128u(sm + SM_QS + 4096 + tid * 16, v1.x & ~1u, v1.y & ~1u, v1.z & ~1u, v1.w & ~1u);
            }
            bar_sync(3, 256);
            STAMP(3);
            float s[4][4];
#pragma unroll
            for (int i = 0; i < 4; i++) s[i][0] = s[i][1] = s[i][2] = s[i][3] = 0.f;
#pragma unroll
            for (int q = 0; q < 4; q++) {
                uint4 qa[4];
#pragma unroll
                for (int i = 0; i < 4; i++) qa[i] = lds128(sm + SM_QS + (4 * q + i) * 512 + lane * 16);
                mbar_wait(sm + SM_BAR + 8 * (B_CKV + q));
                if (q == 3) STAMP(4);
                uint32_t bf[4][4];
#pragma unroll
                for (int i = 0; i < 4; i++) ldsm4((a_s ^ ((i >> 1) << 6)) + q * 16384 + (i & 1) * 1024, bf[i]);
                mma(s[0], qa[0].x, qa[0].y, qa[0].z, qa[0].w, bf[0][0], bf[0][1]);
                mma(s[1], qa[0].x, qa[0].y, qa[0].z, qa[0].w, bf[1][0], bf[1][1]);
                mma(s[2], qa[1].x, qa[1].y, qa[1].z, qa[1].w, bf[0][2], bf[0][3]);
                mma(s[3], qa[1].x, qa[1].y, qa[1].z, qa[1].w, bf[1][2], bf[1][3]);
                mma(s[0], qa[2].x, qa[2].y, qa[2].z, qa[2].w, bf[2][0], bf[2][1]);
                mma(s[1], qa[2].x, qa[2].y, qa[2].z, qa[2].w, bf[3][0], bf[3][1]);
                mma(s[2], qa[3].x, qa[3].y, qa[3].z, qa[3].w, bf[2][2], bf[2][3]);
                mma(s[3], qa[3].x, qa[3].y, qa[3].z, qa[3].w, bf[3][2], bf[3][3]);
            }
            {
                const float u0 = s[0][0] + s[2][0], u1 = s[0][1] + s[2][1], u2 = s[1][0] + s[3][0], u3 = s[1][1] + s[3][1];
                const float v0 = s[0][2] + s[2][2], v1 = s[0][3] + s[2][3], v2 = s[1][2] + s[3][2], v3 = s[1][3] + s[3][3];
                st_async4(smp + SM_SPR + o_spw, u0, u1, u2, u3, smp + SM_BAR + 8 * B_SP);
                st_async4(smp + SM_SPR + 512 + o_spw, v0, v1, v2, v3, smp + SM_BAR + 8 * B_SP);
                sts128(sm + SM_SPL + o_spw, u0, u1, u2, u3);
                sts128(sm + SM_SPL + 512 + o_spw, v0, v1, v2, v3);
            }
            uint32_t ct[4][4][4];
#pragma unroll
            for (int n = 0; n < 4; n++)
#pragma unroll
                for (int kb = 0; kb < 4; kb++) ldsm4t((a_ct ^ (n << 4)) + kb * 4096, ct[n][kb]);
            bar_sync(3, 256);
            STAMP(5);
            {
                const uint4 ul = lds128(a_sr + SM_SPL), vl = lds128(a_sr + SM_SPL + 512);
                mbar_wait(sm + SM_BAR + 8 * B_SP);
                STAMP(6);
                const uint4 ur = lds128(a_sr + SM_SPR), vr = lds128(a_sr + SM_SPR + 512);
                const float u0 = __uint_as_float(ul.x) + __uint_as_float(ur.x), u1 = __uint_as_float(ul.y) + __uint_as_float(ur.y);
                const float u2 = __uint_as_float(ul.z) + __uint_as_float(ur.z), u3 = __uint_as_float(ul.w) + __uint_as_float(ur.w);
                const float v0 = __uint_as_float(vl.x) + __uint_as_float(vr.x), v1 = __uint_as_float(vl.y) + __uint_as_float(vr.y);
                const float v2 = __uint_as_float(vl.z) + __uint_as_float(vr.z), v3 = __uint_as_float(vl.w) + __uint_as_float(vr.w);
                const float mu = warp_max(fmaxf(fmaxf(u0, u1), fmaxf(u2, u3)));
                const float mv = warp_max(fmaxf(fmaxf(v0, v1), fmaxf(v2, v3)));
                const uint32_t a0 = pack_bf16(ex2(u0 - mu), ex2(u1 - mu)), a2 = pack_bf16(ex2(u2 - mu), ex2(u3 - mu));
                const uint32_t a1 = pack_bf16(ex2(v0 - mv), ex2(v1 - mv)), a3 = pack_bf16(ex2(v2 - mv), ex2(v3 - mv));
                sts128u(sm + SM_P + g * 512 + warp * 64 + t * 16, a0, a1, a2, a3);
                bar_sync(3, 256);
                STAMP(7);
                uint4 pa[8];
#pragma unroll
                for (int q = 0; q < 8; q++) pa[q] = lds128(sm + SM_P + q * 512 + lane * 16);
                float o[2][4][4];
#pragma unroll
                for (int n = 0; n < 4; n++)
#pragma unroll
                    for (int e = 0; e < 4; e++) o[0][n][e] = o[1][n][e] = 0.f;
#pragma unroll
                for (int i = 0; i < 4; i++) {
#pragma unroll
                    for (int n = 0; n < 4; n++) mma(o[0][n], pa[2 * i].x, pa[2 * i].y, pa[2 * i].z, pa[2 * i].w, ct[n][i][0], ct[n][i][1]);
#pragma unroll
                    for (int n = 0; n < 4; n++) mma(o[1][n], pa[2 * i + 1].x, pa[2 * i + 1].y, pa[2 * i + 1].z, pa[2 * i + 1].w, ct[n][i][2], ct[n][i][3]);
                }
                const uint32_t q0 = r ? a1 : a0, q1 = r ? a3 : a2;
                float l = (bf_lo(q0) + bf_hi(q0)) + (bf_lo(q1) + bf_hi(q1));
#pragma unroll
                for (int d = 1; d < 32; d <<= 1) l += shfl_x(l, d);
                if (lane < 4) st_pub64(p_stw, tagf(l, tag), __float_as_uint(r ? mv : mu));
                uint32_t w0[4], w1[4];
#pragma unroll
                for (int n = 0; n < 4; n++) {
                    w0[n] = pack_bf16(o[0][n][0] + o[1][n][0], o[0][n][1] + o[1][n][1]);
                    w1[n] = pack_bf16(o[0][n][2] + o[1][n][2], o[0][n][3] + o[1][n][3]);
                }
                st_pub2x64(p_e3w, tagw(w0[0], tag), w0[1], tagw(w0[2], tag), w0[3]);
                st_pub2x64(p_e3w + 8 * 2 * 8 * 32 * 4, tagw(w1[0], tag), w1[1], tagw(w1[2], tag), w1[3]);
            }
        }
        STAMP(8);
        if (ffn) {
            const uint32_t xa = sm + SM_XS + 160 * kq + 4 * t;
            uint32_t xb[5][2];
#pragma unroll
            for (int s = 0; s < 5; s++) { xb[s][0] = lds32(xa + s * 32); xb[s][1] = lds32(xa + s * 32 + 16); }
            mbar_wait(sm + SM_BAR + 8 * (B_W1 + (warp >> 2)));
            uint32_t a[5][4];
#pragma unroll
            for (int s = 0; s < 5; s++) ldsm4t(a_w1 + s * 1024, a[s]);
            float c0[4] = {0.f, 0.f, 0.f, 0.f}, c1[4] = {0.f, 0.f, 0.f, 0.f};
#pragma unroll
            for (int s = 0; s < 5; s++) mma4((s & 1) ? c1 : c0, a[s], xb[s][0], xb[s][1]);
            if (t < 2) st_async1(a_xh, t ? c0[2] + c1[2] : c0[0] + c1[0], b_xh + SM_BAR + 8 * B_XH);
        }
        STAMP(9);
        {
            uint4 v[4];
            uint2 st;
            int it = 0;
            while (true) {
                st = ld_poll64(p_str);
#pragma unroll
                for (int i = 0; i < 4; i++) v[i] = ld_poll2x64(p_e3r + i * 32);
                unsigned bad = st.x ^ tag;
#pragma unroll
                for (int i = 0; i < 4; i++) bad = chk(chk(bad, v[i].x, tag), v[i].z, tag);
                if (!(bad & 1u) || ++it >= SPIN_MAX) break;
                __nanosleep(BACKOFF);
            }
            __syncwarp();
            STAMP(10);
            const float M = warp_max(__uint_as_float(st.y));
            const float f = ex2(__uint_as_float(st.y) - M);
            float L = f * untagf(st.x);
            float acc[8];
#pragma unroll
            for (int e = 0; e < 8; e++) acc[e] = 0.f;
#pragma unroll
            for (int i = 0; i < 4; i++) {
                v[i].x &= ~1u; v[i].z &= ~1u;
                fma8(acc, __shfl_sync(0xffffffffu, f, 8 * i + g), v[i]);
            }
#pragma unroll
            for (int d = 1; d < 32; d <<= 1) L += shfl_x(L, d);
            const bool b4 = lane & 16, b3 = lane & 8, b2 = lane & 4;
            float k4[4], k2[2];
#pragma unroll
            for (int e = 0; e < 4; e++) k4[e] = (b4 ? acc[4 + e] : acc[e]) + shfl_x(b4 ? acc[e] : acc[4 + e], 16);
#pragma unroll
            for (int e = 0; e < 2; e++) k2[e] = (b3 ? k4[2 + e] : k4[e]) + shfl_x(b3 ? k4[e] : k4[2 + e], 8);
            const float s = __fdividef((b2 ? k2[1] : k2[0]) + shfl_x(b2 ? k2[0] : k2[1], 4), L);
            const uint32_t hi = pack_bf16(s, 0.f);
            sts16(a_vf3w, hi);
            sts16(a_vf3w + 576, pack_bf16(s - bf_lo(hi), 0.f));
        }
        {
            uint32_t a[8][4];
#pragma unroll
            for (int i = 0; i < 2; i++) {
                mbar_wait(sm + SM_BAR + 8 * (B_WUV + 2 * (warp >> 2) + i));
#pragma unroll
                for (int s = 0; s < 4; s++) ldsm4t(a_wuv + (4 * i + s) * 2048, a[4 * i + s]);
            }
            bar_sync(3, 256);
            STAMP(11);
            uint4 bv[4];
#pragma unroll
            for (int i = 0; i < 4; i++) bv[i] = lds128(a_vf3r + i * 16);
            float c[4][4];
#pragma unroll
            for (int i = 0; i < 4; i++) {
                c[i][0] = c[i][1] = c[i][2] = c[i][3] = 0.f;
                mma4(c[i], a[2 * i], bv[i].x, bv[i].y);
            }
#pragma unroll
            for (int i = 0; i < 4; i++) mma4(c[i], a[2 * i + 1], bv[i].z, bv[i].w);
            float e0[4];
#pragma unroll
            for (int i = 0; i < 4; i++) e0[i] = (t & 1) ? c[i][2] + c[i][3] : c[i][0] + c[i][1];
            if (t < 2) st_async1(a_xc, (e0[0] + e0[1]) + (e0[2] + e0[3]), b_xc + SM_BAR + 8 * B_XC);
        }
        STAMP(12);
        {
            float c[5][4];
#pragma unroll
            for (int i = 0; i < 5; i++) c[i][0] = c[i][1] = c[i][2] = c[i][3] = 0.f;
            const int half = warp >> 2;
            const float gt = __uint_as_float(lds32(sm + SM_G));
            if (ffn) {
                mbar_wait(sm + SM_BAR + 8 * B_XH);
                const uint4 u = lds128(sm + SM_XH + (lane & 15) * 32), v = lds128(sm + SM_XH + (lane & 15) * 32 + 16);
                float hv = ((__uint_as_float(u.x) + __uint_as_float(u.y)) + (__uint_as_float(u.z) + __uint_as_float(u.w))) +
                           ((__uint_as_float(v.x) + __uint_as_float(v.y)) + (__uint_as_float(v.z) + __uint_as_float(v.w)));
                hv = bf_lo(pack_bf16(hv, 0.f));
                hv = __fdividef(hv, 1.f + __expf(-hv)) * (1.f - gt);
                const uint32_t w = pack_bf16(hv, shfl_x(hv, 1));
                const uint32_t b0 = __shfl_sync(0xffffffffu, w, 2 * t), b1 = __shfl_sync(0xffffffffu, w, 8 + 2 * t);
                mbar_wait(sm + SM_BAR + 8 * (B_W2 + half));
                uint32_t a[5][4];
#pragma unroll
                for (int i = 0; i < 5; i++) ldsm4t(a_fin[i] + SM_W2, a[i]);
#pragma unroll
                for (int i = 0; i < 5; i++) mma4(c[i], a[i], b0, b1);
            }
            mbar_wait(sm + SM_BAR + 8 * B_XC);
            STAMP(13);
            const uint4 u = lds128(sm + SM_XC + lane * 16);
            const float cv = ((__uint_as_float(u.x) + __uint_as_float(u.y)) + (__uint_as_float(u.z) + __uint_as_float(u.w))) * gt;
            const uint32_t w = pack_bf16(cv, shfl_x(cv, 1));
            uint32_t bb[4];
#pragma unroll
            for (int q = 0; q < 4; q++) bb[q] = __shfl_sync(0xffffffffu, w, 8 * q + 2 * t);
#pragma unroll
            for (int s = 0; s < 2; s++) {
                mbar_wait(sm + SM_BAR + 8 * (B_WO + 2 * s + half));
                uint32_t a[5][4];
#pragma unroll
                for (int i = 0; i < 5; i++) ldsm4t(a_fin[i] + SM_WO + s * 20480, a[i]);
#pragma unroll
                for (int i = 0; i < 5; i++) mma4(c[i], a[i], bb[2 * s], bb[2 * s + 1]);
            }
            STAMP_T(224, 14);
            const bool t0 = t & 1, t1 = t & 2;
            const float v0 = t1 ? (t0 ? c[1][2] : c[1][0]) : (t0 ? c[0][2] : c[0][0]);
            const float v1 = t1 ? (t0 ? c[3][2] : c[3][0]) : (t0 ? c[2][2] : c[2][0]);
            const float v2 = t0 ? c[4][2] : c[4][0];
            st_pub1(p_e4w, tagf(v0, tag));
            st_pub1(p_e4w + 4 * NCTA * 8, tagf(v1, tag));
            if (!t1) st_pub1(p_e4w + 8 * NCTA * 8, tagf(v2, tag));
        }
        STAMP_T(224, 15);
    } else if (warp == 8) {
        const unsigned t0 = gtimer();
        const uint32_t bar = sm + SM_BAR + 8 * lane;
        if (lane == 0) {
#pragma unroll
            for (int i = 0; i < NBAR; i++) asm volatile("mbarrier.init.shared::cta.b64 [%0], 1;" :: "r"(sm + SM_BAR + 8 * i) : "memory");
            asm volatile("mbarrier.arrive.expect_tx.shared::cta.b64 _, [%0], 8192;" :: "r"(sm + SM_BAR + 8 * B_SP) : "memory");
            asm volatile("mbarrier.arrive.expect_tx.shared::cta.b64 _, [%0], 512;" :: "r"(sm + SM_BAR + 8 * B_XC) : "memory");
            asm volatile("mbarrier.arrive.expect_tx.shared::cta.b64 _, [%0], 512;" :: "r"(sm + SM_BAR + 8 * B_XH) : "memory");
            asm volatile("fence.mbarrier_init.release.cluster;" ::: "memory");
        }
        __syncwarp();
        asm volatile("barrier.cluster.arrive.relaxed.aligned;" ::: "memory");
        bar_arrive(1, 320);
        if (lane < 6) asm volatile("prefetch.tensormap [%0];" :: "l"(&P.m[lane]) : "memory");
        {
            int map, c0 = 0, c1, c2;
            uint32_t dst, bytes, due;
            const int k = lane;
            constexpr int DF = DT_NS * 135 / 128;
            if (k < B_CKV)      { map = 0; c1 = 128 * j + 32 * k;            c2 = 2 * h;              dst = SM_WUK + k * 8192;            bytes = 8192;  due = k * DT_NS; }
            else if (k < B_W1)  { map = 1; c1 = 128 * h;                     c2 = 4 * r + k - B_CKV;  dst = SM_CKV + (k - B_CKV) * 16384; bytes = 16384; due = k * DT_NS; }
            else if (k < B_WUV) { map = 2; c1 = 320 * r + 160 * (k - B_W1);  c2 = h; c0 = 32 * pp;    dst = SM_W1 + (k - B_W1) * 10240;   bytes = ffn ? 10240 : 0; due = 8 * DT_NS + (k - B_W1) * DF; }
            else if (k < B_W2)  { map = 3; c1 = 256 * r + 64 * (k - B_WUV);  c2 = 2 * h + pp;         dst = SM_WUV + (k - B_WUV) * 8192;  bytes = 8192;  due = (k - 2) * DT_NS + 2 * DF; }
            else if (k < B_WO)  { map = 4; c1 = 16 * b;                      c2 = 5 * (k - B_W2);     dst = SM_W2 + (k - B_W2) * 10240;   bytes = ffn ? 10240 : 0; due = 12 * DT_NS + (k - 12) * DF; }
            else                { map = 5; c1 = 32 * b + 16 * ((k - B_WO) >> 1); c2 = 5 * (k & 1);    dst = SM_WO + (k - B_WO) * 10240;   bytes = k < B_SP ? 10240 : 0;
                                  due = 12 * DT_NS + 4 * DF + (k - B_WO) * (DT_NS * 5 / 4); }
            due += T0_NS;
            bool pending = bytes != 0;
            if (pending) asm volatile("mbarrier.arrive.expect_tx.shared::cta.b64 _, [%0], %1;" :: "r"(bar), "r"(bytes) : "memory");
            STAMP_T(256, 21);
            while (__any_sync(0xffffffffu, pending)) {
                const unsigned now = gtimer() - t0;
                if (pending && now >= due) {
                    asm volatile("cp.async.bulk.tensor.3d.shared::cluster.global.mbarrier::complete_tx::bytes [%0], [%1, {%3,%4,%5}], [%2];"
                                 :: "r"(sm + dst), "l"(&P.m[map]), "r"(bar), "r"(c0), "r"(c1), "r"(c2) : "memory");
                    pending = false;
                }
            }
        }
        STAMP_T(256, 22);
        if (b < 80) {
            const uint4* p = S->e4 + b * NCTA * 2 + lane;
            mbar_wait(sm + SM_BAR + 8 * B_XC);
            const unsigned tag = lds32(sm + SM_G + 4);
            mbar_wait(sm + SM_BAR + 8 * (B_WO + 3));
            STAMP_T(256, 16);
            uint4 v[8];
            int it = 0;
            while (true) {
#pragma unroll
                for (int i = 0; i < 8; i++) v[i] = ld_poll4(p + i * 32);
                unsigned bad0 = 0u, bad1 = 0u;
#pragma unroll
                for (int i = 0; i < 4; i++) { bad0 = chk4(bad0, v[i], tag); bad1 = chk4(bad1, v[4 + i], tag); }
                if (!((bad0 | bad1) & 1u) || ++it >= SPIN_MAX) break;
            }
            __syncwarp();
#define SUM8(f) (((untagf(v[0].f) + untagf(v[1].f)) + (untagf(v[2].f) + untagf(v[3].f))) + ((untagf(v[4].f) + untagf(v[5].f)) + (untagf(v[6].f) + untagf(v[7].f))))
            const float s0 = SUM8(x), s1 = SUM8(y), s2 = SUM8(z), s3 = SUM8(w);
#undef SUM8
            const bool b4 = lane & 16, b3 = lane & 8;
            const float k0 = (b4 ? s2 : s0) + shfl_x(b4 ? s0 : s2, 16);
            const float k1 = (b4 ? s3 : s1) + shfl_x(b4 ? s1 : s3, 16);
            float s = (b3 ? k1 : k0) + shfl_x(b3 ? k0 : k1, 8);
            s += shfl_x(s, 4);
            s += shfl_x(s, 2);
            if (!(lane & 6)) P.out[b * 8 + (lane & 1) * 4 + (lane >> 3)] = __float2bfloat16(s);
            if (b == 0 && lane == 0) st_pub1(&S->epoch, tag);
            STAMP_T(256, 17);
        }
    } else {
        const unsigned old = ld_poll1(&S->epoch) & 1u;
        uint32_t xv[10], gw[10];
#pragma unroll
        for (int i = 0; i < 10; i++) {
            xv[i] = ldg32(P.x + (i * 32 + lane) * 2);
            gw[i] = ldg32(P.gate + (i * 32 + lane) * 2);
        }
        asm volatile("barrier.cluster.arrive.relaxed.aligned;" ::: "memory");
        st_pub4(&S->e1[b * 128 + lane * 4], old, old, old, old);
        {
            unsigned* p2 = reinterpret_cast<unsigned*>(S->e2) +
                           (((((h >> 4) * 2 + pp) * 16 + 8 * r + (lane >> 2)) * 32) + (h & 7) * 4 + (lane & 3)) * 4 + ((h >> 3) & 1);
            st_pub1(p2, old);
            st_pub1(p2 + 2, old);
        }
        if (lane == 0) sts32(sm + SM_G + 4, old ^ 1u);
        bar_arrive(1, 320);
        STAMP_T(288, 18);
#pragma unroll
        for (int i = 0; i < 5; i++) st_pub4(&S->e4[((i * 16 + (lane >> 1)) * NCTA + b) * 2 + (lane & 1)], old, old, old, old);
        float z = 0.f;
#pragma unroll
        for (int i = 0; i < 10; i++) {
            if ((i >= 5) == (r != 0)) sts32(sm + SM_XS + ((i % 5) * 32 + lane) * 4, xv[i]);
            z = fmaf(bf_lo(xv[i]), bf_lo(gw[i]), z);
            z = fmaf(bf_hi(xv[i]), bf_hi(gw[i]), z);
        }
#pragma unroll
        for (int d = 1; d < 32; d <<= 1) z += shfl_x(z, d);
        if (lane == 0) sts32(sm + SM_G, __float_as_uint(__fdividef(1.f, 1.f + __expf(-z))));
        bar_arrive(2, 288);
        STAMP_T(288, 23);
    }
}

typedef CUresult (*EncodeFn)(CUtensorMap*, CUtensorMapDataType, cuuint32_t, void*, const cuuint64_t*, const cuuint64_t*,
                             const cuuint32_t*, const cuuint32_t*, CUtensorMapInterleave, CUtensorMapSwizzle,
                             CUtensorMapL2promotion, CUtensorMapFloatOOBfill);

void make_map(EncodeFn enc, CUtensorMap* m, const void* base, int rows, int cols, int box_cols, int box_rows, int box_blks) {
    cuuint64_t gd[3] = {64, (cuuint64_t)rows, (cuuint64_t)(cols / 64)};
    cuuint64_t gs[2] = {(cuuint64_t)cols * 2, 128};
    cuuint32_t bd[3] = {(cuuint32_t)box_cols, (cuuint32_t)box_rows, (cuuint32_t)box_blks};
    cuuint32_t es[3] = {1, 1, 1};
    enc(m, CU_TENSOR_MAP_DATA_TYPE_BFLOAT16, 3, const_cast<void*>(base), gd, gs, bd, es, CU_TENSOR_MAP_INTERLEAVE_NONE,
        box_cols == 64 ? CU_TENSOR_MAP_SWIZZLE_128B : CU_TENSOR_MAP_SWIZZLE_64B,
        box_cols == 64 ? CU_TENSOR_MAP_L2_PROMOTION_NONE : CU_TENSOR_MAP_L2_PROMOTION_L2_128B, CU_TENSOR_MAP_FLOAT_OOB_FILL_NONE);
}

}

extern "C" void kernel_launch(void* const* d_in, const int* in_sizes, int n_in, void* d_out, int out_size) {
    (void)in_sizes; (void)n_in; (void)out_size;
    constexpr int smem_bytes = SMEM_BYTES;
    static EncodeFn enc = nullptr;
    static Scratch* scratch = nullptr;
    if (!enc) {
        void* fn = nullptr;
        cudaDriverEntryPointQueryResult st;
        cudaGetDriverEntryPoint("cuTensorMapEncodeTiled", &fn, cudaEnableDefault, &st);
        enc = (EncodeFn)fn;
        cudaFuncSetAttribute(fused_kernel, cudaFuncAttributeMaxDynamicSharedMemorySize, smem_bytes);
        cudaGetSymbolAddress((void**)&scratch, g_s);
    }
    Params p;
    make_map(enc, &p.m[0], d_in[3], 512, 4096, 64, 32, 2);
    make_map(enc, &p.m[1], d_in[1], 4096, 512, 64, 128, 1);
    make_map(enc, &p.m[2], d_in[7], 640, 1728, 32, 160, 1);
    make_map(enc, &p.m[3], d_in[4], 512, 4096, 64, 64, 1);
    make_map(enc, &p.m[4], d_in[8], 1728, 640, 64, 16, 5);
    make_map(enc, &p.m[5], d_in[5], 4096, 640, 64, 16, 5);
    p.x = (const __nv_bfloat16*)d_in[0];
    p.wq = (const __nv_bfloat16*)d_in[2];
    p.gate = (const __nv_bfloat16*)d_in[9];
    p.out = (__nv_bfloat16*)d_out;
    p.s = scratch;
    fused_kernel<<<NCTA, NTHREADS, smem_bytes>>>(p);
}
```

```cpp
#include <cuda_runtime.h>
#include <cuda.h>
#include <cuda_bf16.h>
#include <stdint.h>

namespace {

constexpr int NCTA = 128;
constexpr int NTHREADS = 320;
constexpr int SPIN_MAX = 1 << 18;

constexpr int SM_WUK = 0;
constexpr int SM_CKV = SM_WUK + 32768;
constexpr int SM_WUV = SM_CKV + 65536;
constexpr int SM_W1  = SM_WUV + 32768;
constexpr int SM_W2  = SM_W1 + 20480;
constexpr int SM_WO  = SM_W2 + 20480;
constexpr int SM_SPR = SM_WO + 40960;
constexpr int SM_QS  = SM_WUK;
constexpr int SM_SPL = SM_WUK + 8192;
constexpr int SM_P   = SM_WUK + 16384;
constexpr int SM_FIN = SM_WUK + 24576;
constexpr int SM_XQ  = SM_SPR + 8192;
constexpr int SM_XS  = SM_XQ + 4096;
constexpr int SM_XC  = SM_XS + 640;
constexpr int SM_XH  = SM_XC + 2048;
constexpr int SM_G   = SM_XH + 512;
constexpr int SM_BAR = SM_G + 32;
constexpr int SM_END = SM_BAR + 32 * 8;
constexpr int SMEM_BYTES = SM_END;
static_assert(SMEM_BYTES <= 232448 - 256, "smem");

constexpr int B_WUK = 0, B_CKV = 4, B_W1 = 8, B_WUV = 10, B_W2 = 14, B_WO = 16, B_SP = 20, B_XC = 21, B_XH = 22, B_XQ = 23, NBAR = 24;

struct Scratch {
    uint4    e3[32 * 2 * 8 * 32 * 4];
    uint4    e4[80 * NCTA * 2];
    uint4    e2[2 * 32 * 64];
    uint2    st[32 * 32 * 4];
    unsigned epoch;
};
__device__ __align__(1024) Scratch g_s;

struct Params {
    const __nv_bfloat16* wq;
    const __nv_bfloat16* x;
    Scratch* s;
    const __nv_bfloat16* gate;
    __nv_bfloat16* out;
    alignas(64) CUtensorMap m[6];
};

#define STAMP(i)
#define STAMP_T(t, i)

__device__ __forceinline__ unsigned clock32() { unsigned c; asm volatile("mov.u32 %0, %%clock;" : "=r"(c) :: "memory"); return c; }
__device__ __forceinline__ unsigned gtimer() { unsigned c; asm volatile("mov.u32 %0, %%globaltimer_lo;" : "=r"(c) :: "memory"); return c; }

__device__ __forceinline__ uint4 ldg_stream(const void* p) {
    uint4 v;
    asm volatile("ld.global.nc.L1::no_allocate.v4.u32 {%0,%1,%2,%3}, [%4];"
                 : "=r"(v.x), "=r"(v.y), "=r"(v.z), "=r"(v.w) : "l"(p));
    return v;
}
__device__ __forceinline__ uint4 ld_poll4(const void* p) {
    uint4 v;
    asm volatile("ld.relaxed.gpu.global.v4.u32 {%0,%1,%2,%3}, [%4];"
                 : "=r"(v.x), "=r"(v.y), "=r"(v.z), "=r"(v.w) : "l"(p) : "memory");
    return v;
}
__device__ __forceinline__ uint4 ld_poll2x64(const void* p) {
    uint4 v;
    asm volatile("{.reg .b64 a, b; ld.relaxed.gpu.global.v2.b64 {a, b}, [%4]; mov.b64 {%0,%1}, a; mov.b64 {%2,%3}, b;}"
                 : "=r"(v.x), "=r"(v.y), "=r"(v.z), "=r"(v.w) : "l"(p) : "memory");
    return v;
}
__device__ __forceinline__ uint2 ld_poll64(const void* p) {
    uint2 v;
    asm volatile("{.reg .b64 a; ld.relaxed.gpu.global.b64 a, [%2]; mov.b64 {%0,%1}, a;}" : "=r"(v.x), "=r"(v.y) : "l"(p) : "memory");
    return v;
}
__device__ __forceinline__ unsigned ld_poll1(const void* p) {
    unsigned v;
    asm volatile("ld.relaxed.gpu.global.u32 %0, [%1];" : "=r"(v) : "l"(p) : "memory");
    return v;
}
__device__ __forceinline__ void st_pub2x64(void* p, unsigned a, unsigned b, unsigned c, unsigned d) {
    asm volatile("{.reg .b64 x, y; mov.b64 x, {%1,%2}; mov.b64 y, {%3,%4}; st.relaxed.gpu.global.v2.b64 [%0], {x, y};}"
                 :: "l"(p), "r"(a), "r"(b), "r"(c), "r"(d) : "memory");
}
__device__ __forceinline__ void st_pub64(void* p, unsigned a, unsigned b) {
    asm volatile("{.reg .b64 x; mov.b64 x, {%1,%2}; st.relaxed.gpu.global.b64 [%0], x;}" :: "l"(p), "r"(a), "r"(b) : "memory");
}
__device__ __forceinline__ void st_pub1(void* p, unsigned a) {
    asm volatile("st.relaxed.gpu.global.u32 [%0], %1;" :: "l"(p), "r"(a) : "memory");
}
__device__ __forceinline__ unsigned tagw(unsigned w, unsigned tag) { return (w & ~1u) | tag; }
__device__ __forceinline__ unsigned tagf(float v, unsigned tag) { return (__float_as_uint(v) & ~1u) | tag; }
__device__ __forceinline__ float untagf(unsigned w) { return __uint_as_float(w & ~1u); }

__device__ __forceinline__ void mbar_wait(uint32_t bar) {
    uint32_t ok;
    int it = 0;
#pragma unroll 1
    do {
        asm volatile("{.reg .pred p; mbarrier.try_wait.parity.shared::cta.b64 p, [%1], 0; selp.u32 %0,1,0,p;}"
                     : "=r"(ok) : "r"(bar) : "memory");
    } while (!ok && ++it < SPIN_MAX);
}
__device__ __forceinline__ void bar_sync(int id, int n) { asm volatile("bar.sync %0, %1;" :: "r"(id), "r"(n) : "memory"); }
__device__ __forceinline__ void bar_arrive(int id, int n) { asm volatile("bar.arrive %0, %1;" :: "r"(id), "r"(n) : "memory"); }
__device__ __forceinline__ uint32_t mapa(uint32_t a, uint32_t rank) {
    uint32_t r;
    asm("mapa.shared::cluster.u32 %0, %1, %2;" : "=r"(r) : "r"(a), "r"(rank));
    return r;
}
__device__ __forceinline__ void st_async4(uint32_t a, float x, float y, float z, float w, uint32_t bar) {
    asm volatile("st.async.weak.shared::cluster.mbarrier::complete_tx::bytes.v4.f32 [%0], {%1,%2,%3,%4}, [%5];"
                 :: "r"(a), "f"(x), "f"(y), "f"(z), "f"(w), "r"(bar) : "memory");
}
__device__ __forceinline__ void st_async2(uint32_t a, uint32_t x, uint32_t y, uint32_t bar) {
    asm volatile("st.async.weak.shared::cluster.mbarrier::complete_tx::bytes.v2.b32 [%0], {%1,%2}, [%3];"
                 :: "r"(a), "r"(x), "r"(y), "r"(bar) : "memory");
}

__device__ __forceinline__ void ldsm4(uint32_t a, uint32_t (&r)[4]) {
    asm volatile("ldmatrix.sync.aligned.m8n8.x4.shared.b16 {%0,%1,%2,%3}, [%4];"
                 : "=r"(r[0]), "=r"(r[1]), "=r"(r[2]), "=r"(r[3]) : "r"(a) : "memory");
}
__device__ __forceinline__ void ldsm4t(uint32_t a, uint32_t (&r)[4]) {
    asm volatile("ldmatrix.sync.aligned.m8n8.x4.trans.shared.b16 {%0,%1,%2,%3}, [%4];"
                 : "=r"(r[0]), "=r"(r[1]), "=r"(r[2]), "=r"(r[3]) : "r"(a) : "memory");
}
__device__ __forceinline__ void mma(float (&c)[4], uint32_t a0, uint32_t a1, uint32_t a2, uint32_t a3, uint32_t b0, uint32_t b1) {
    asm("mma.sync.aligned.m16n8k16.row.col.f32.bf16.bf16.f32 {%0,%1,%2,%3}, {%4,%5,%6,%7}, {%8,%9}, {%0,%1,%2,%3};"
        : "+f"(c[0]), "+f"(c[1]), "+f"(c[2]), "+f"(c[3])
        : "r"(a0), "r"(a1), "r"(a2), "r"(a3), "r"(b0), "r"(b1));
}
__device__ __forceinline__ uint32_t pack_bf16(float lo, float hi) {
    uint32_t r;
    asm("cvt.rn.bf16x2.f32 %0, %1, %2;" : "=r"(r) : "f"(hi), "f"(lo));
    return r;
}
__device__ __forceinline__ float bf_lo(uint32_t w) { return __uint_as_float(w << 16); }
__device__ __forceinline__ float bf_hi(uint32_t w) { return __uint_as_float(w & 0xFFFF0000u); }
__device__ __forceinline__ float ex2(float x) { float y; asm("ex2.approx.ftz.f32 %0, %1;" : "=f"(y) : "f"(x)); return y; }
__device__ __forceinline__ uint4 lds128(uint32_t a) {
    uint4 v;
    asm volatile("ld.shared.v4.u32 {%0,%1,%2,%3}, [%4];" : "=r"(v.x), "=r"(v.y), "=r"(v.z), "=r"(v.w) : "r"(a) : "memory");
    return v;
}
__device__ __forceinline__ float2 lds64f(uint32_t a) {
    float2 v;
    asm volatile("ld.shared.v2.f32 {%0,%1}, [%2];" : "=f"(v.x), "=f"(v.y) : "r"(a) : "memory");
    return v;
}
__device__ __forceinline__ uint32_t lds32(uint32_t a) {
    uint32_t v;
    asm volatile("ld.shared.u32 %0, [%1];" : "=r"(v) : "r"(a) : "memory");
    return v;
}
__device__ __forceinline__ void sts128(uint32_t a, float x, float y, float z, float w) {
    asm volatile("st.shared.v4.f32 [%0], {%1,%2,%3,%4};" :: "r"(a), "f"(x), "f"(y), "f"(z), "f"(w) : "memory");
}
__device__ __forceinline__ void sts64(uint32_t a, uint32_t x, uint32_t y) {
    asm volatile("st.shared.v2.u32 [%0], {%1,%2};" :: "r"(a), "r"(x), "r"(y) : "memory");
}
__device__ __forceinline__ void sts32(uint32_t a, uint32_t x) {
    asm volatile("st.shared.u32 [%0], %1;" :: "r"(a), "r"(x) : "memory");
}
__device__ __forceinline__ void sts16(uint32_t a, uint32_t x) {
    asm volatile("st.shared.u16 [%0], %1;" :: "r"(a), "h"((unsigned short)x) : "memory");
}
__device__ __forceinline__ void fma8(float (&acc)[8], float s, const uint4& v) {
    acc[0] = fmaf(s, bf_lo(v.x), acc[0]); acc[1] = fmaf(s, bf_hi(v.x), acc[1]);
    acc[2] = fmaf(s, bf_lo(v.y), acc[2]); acc[3] = fmaf(s, bf_hi(v.y), acc[3]);
    acc[4] = fmaf(s, bf_lo(v.z), acc[4]); acc[5] = fmaf(s, bf_hi(v.z), acc[5]);
    acc[6] = fmaf(s, bf_lo(v.w), acc[6]); acc[7] = fmaf(s, bf_hi(v.w), acc[7]);
}
__device__ __forceinline__ float warp_max(float v) {
    int k = __float_as_int(v);
    k ^= (k >> 31) & 0x7FFFFFFF;
    asm("redux.sync.max.s32 %0, %0, 0xffffffff;" : "+r"(k));
    k ^= (k >> 31) & 0x7FFFFFFF;
    return __int_as_float(k);
}

__device__ __forceinline__ void st_async1(uint32_t a, float x, uint32_t bar) {
    asm volatile("st.async.weak.shared::cluster.mbarrier::complete_tx::bytes.f32 [%0], %1, [%2];" :: "r"(a), "f"(x), "r"(bar) : "memory");
}
__device__ __forceinline__ void st_pub4(void* p, unsigned a, unsigned b, unsigned c, unsigned d) {
    asm volatile("st.relaxed.gpu.global.v4.u32 [%0], {%1,%2,%3,%4};" :: "l"(p), "r"(a), "r"(b), "r"(c), "r"(d) : "memory");
}
__device__ __forceinline__ uint32_t ldg32(const void* p) {
    uint32_t v;
    asm volatile("ld.global.nc.u32 %0, [%1];" : "=r"(v) : "l"(p));
    return v;
}
__device__ __forceinline__ void mma4(float (&c)[4], const uint32_t (&a)[4], uint32_t b0, uint32_t b1) { mma(c, a[0], a[1], a[2], a[3], b0, b1); }
__device__ __forceinline__ float shfl_x(float v, int m) { return __shfl_xor_sync(0xffffffffu, v, m); }
__device__ __forceinline__ unsigned chk(unsigned acc, unsigned w, unsigned tag) {
    unsigned d;
    asm("lop3.b32 %0, %1, %2, %3, 0xF6;" : "=r"(d) : "r"(acc), "r"(w), "r"(tag));
    return d;
}
__device__ __forceinline__ unsigned chk4(unsigned acc, const uint4& v, unsigned tag) { return chk(chk(chk(chk(acc, v.x, tag), v.y, tag), v.z, tag), v.w, tag); }
__device__ __forceinline__ void sts128u(uint32_t a, uint32_t x, uint32_t y, uint32_t z, uint32_t w) {
    asm volatile("st.shared.v4.u32 [%0], {%1,%2,%3,%4};" :: "r"(a), "r"(x), "r"(y), "r"(z), "r"(w) : "memory");
}
__device__ __forceinline__ uint32_t add_bf16x2(uint32_t a, uint32_t b) {
    uint32_t d;
    asm("add.rn.bf16x2 %0, %1, %2;" : "=r"(d) : "r"(a & ~1u), "r"(b & ~1u));
    return d;
}
__device__ __forceinline__ void spin_until(unsigned t) { while ((int)(clock32() - t) < 0) {} }
__device__ __forceinline__ uint32_t fma_bf16x2(uint32_t a, uint32_t b, uint32_t c) {
    uint32_t d;
    asm("fma.rn.bf16x2 %0, %1, %2, %3;" : "=r"(d) : "r"(a), "r"(b), "r"(c));
    return d;
}
__device__ __forceinline__ uint32_t mul_bf16x2(uint32_t a, uint32_t b) {
    uint32_t d;
    asm("mul.rn.bf16x2 %0, %1, %2;" : "=r"(d) : "r"(a), "r"(b));
    return d;
}
__device__ __forceinline__ bool mbar_test(uint32_t bar) {
    uint32_t ok;
    asm volatile("{.reg .pred p; mbarrier.test_wait.parity.shared::cta.b64 p, [%1], 0; selp.u32 %0,1,0,p;}" : "=r"(ok) : "r"(bar) : "memory");
    return __all_sync(0xffffffffu, ok);
}
#define PIN(x) asm volatile("" : "+r"(x))
#define PINL(x) asm volatile("" : "+l"(x))

#define SCHED {1420, 185, 405, 315, 435, 360, 360, 390, 295, 353, 213, 265, 235, 430, 210, 423, 503, 431, 291, 391}
#define STAG_A 285
#define STAG_B 345
#define D3 1600
#define D4 400
#define STS_ 1
#define T0_NS 1400
#define DT_NS 325
#define QGATE_A 0
#define QGATE_B 2
#define CT_EARLY 0
#define DS 700
#define PROF_ROUNDS(k, it)
#define DT2_NS DT_NS

__global__ void __cluster_dims__(2, 1, 1) __launch_bounds__(NTHREADS, 1)
fused_kernel(const __grid_constant__ Params P)
{
    extern __shared__ __align__(1024) unsigned char smem_raw[];
    const int tid = threadIdx.x;
    const int b = blockIdx.x;
    const int h = b >> 2;
    const int r = b & 1, pp = (b >> 1) & 1;
    uint4 wv[10];
    uint32_t xw[5];
    if (tid < 256) {
        asm volatile("barrier.cluster.arrive.relaxed.aligned;" ::: "memory");
        const int m0 = 320 * r + 10 * (tid >> 3);
        const __nv_bfloat16* wp = P.wq + (size_t)m0 * 4096 + (b >> 1) * 64 + (tid & 7) * 8;
#pragma unroll
        for (int i = 0; i < 10; i++) wv[i] = ldg_stream(wp + i * 4096);
#pragma unroll
        for (int i = 0; i < 5; i++) xw[i] = ldg32(P.x + m0 + 2 * i);
    }
    const int warp = tid >> 5, lane = tid & 31;
    const uint32_t sm = (uint32_t)__cvta_generic_to_shared(smem_raw);
    const bool ffn = h < 27;
    Scratch* const S = P.s;

    if (warp < 8) {
        const int g = lane >> 2, t = lane & 3, l7 = lane & 7;
        const int kq = warp >> 1, nh = warp & 1;
        const uint32_t smp = mapa(sm, r ^ 1);
        const int row1 = 2 * l7 + ((lane >> 3) & 1);
        uint32_t a_wuk = sm + SM_WUK + (32 * warp + row1) * 128 + (((lane >> 4) ^ (row1 & 7)) << 4);
        unsigned* p_e2w = reinterpret_cast<unsigned*>(S->e2) + (pp * 32 + h) * 256 + 128 * r + 16 * warp + 8 * (t & 1) + g;
        const uint4* p_e2r = S->e2 + (16 * pp + (tid >> 4)) * 64 + 32 * r + (tid & 15);
        uint32_t a_qsw = sm + SM_QS + (tid >> 4) * 512 + (((tid & 15) ^ ((tid >> 4) & 7)) << 4);
        uint32_t a_qsr = sm + SM_QS + (lane & 15) * 512 + (((lane >> 4) ^ l7) << 4);
        uint32_t a_s = sm + SM_CKV + (16 * warp + l7) * 128 + (((lane >> 3) ^ l7) << 4);
        uint32_t o_spw = warp * 1024 + ((lane ^ (nh << 2)) << 4);
        uint32_t a_ct = sm + SM_CKV + kq * 16384 + lane * 128 + (((4 * nh) ^ l7) << 4);
        uint32_t a_sr = sm + g * 1024 + ((warp ^ (g & 1)) << 6) + t * 16;
        uint2* p_stw = S->st + ((16 * pp + 8 * r + warp) * 32 + h) * STS_ + lane;
        uint4* p_e3w = S->e3 + ((((16 * pp + g) * 2 + r) * 8 + warp) * 32 + h) * 4 + t;
        const uint4* p_e3r = S->e3 + ((h * 2 + r) * 8 + warp) * 128 + lane;
        const uint2* p_str = S->st + (h * 32 + lane) * STS_;
        const int krow = l7 + 8 * (lane >> 4), csel = (lane >> 3) & 1;
        uint32_t a_w1 = sm + SM_W1 + (80 * kq + krow) * 64 + (((2 * nh + csel) ^ (l7 >> 1)) << 4);
        uint32_t a_wuv = sm + SM_WUV + (32 * warp + krow) * 128 + ((csel ^ l7) << 4);
        uint32_t a_fin[5];
#pragma unroll
        for (int i = 0; i < 5; i++) {
            const int N = 10 * (warp & 3) + 2 * i + csel;
            a_fin[i] = sm + (warp >> 2) * 10240 + (N >> 3) * 2048 + krow * 128 + (((N & 7) ^ l7) << 4);
            PIN(a_fin[i]);
        }
        uint32_t b_xc = ((t >> 1) == r ? mapa(sm, r) : smp), b_xh = (nh == r ? mapa(sm, r) : smp);
        uint32_t a_xc = b_xc + SM_XC + (8 * r + warp) * 128 + ((t & 1) * 8 + g) * 8;
        uint32_t a_xh = b_xh + SM_XH + ((t & 1) * 8 + g) * 32 + (4 * r + kq) * 4;
        unsigned* p_e4w = reinterpret_cast<unsigned*>(S->e4) + ((10 * warp + t) * NCTA + b) * 8 + g;
        PIN(a_wuk); PINL(p_e2w); PINL(p_e2r); PIN(a_s); PIN(a_qsw); PIN(a_qsr); PIN(o_spw); PIN(a_ct); PIN(a_sr);
        PINL(p_stw); PINL(p_e3w); PINL(p_e3r); PINL(p_str); PIN(a_w1); PIN(a_wuv); PIN(a_xc); PIN(a_xh); PINL(p_e4w);

        {
            float acc[8];
#pragma unroll
            for (int e = 0; e < 8; e++) acc[e] = 0.f;
#pragma unroll
            for (int i = 0; i < 10; i++) fma8(acc, (i & 1) ? bf_hi(xw[i >> 1]) : bf_lo(xw[i >> 1]), wv[i]);
            const bool b4 = lane & 16, b3 = lane & 8;
            float k4[4], k2[2];
#pragma unroll
            for (int e = 0; e < 4; e++) k4[e] = (b4 ? acc[4 + e] : acc[e]) + shfl_x(b4 ? acc[e] : acc[4 + e], 16);
#pragma unroll
            for (int e = 0; e < 2; e++) k2[e] = (b3 ? k4[2 + e] : k4[e]) + shfl_x(b3 ? k4[e] : k4[2 + e], 8);
            STAMP(0);
            asm volatile("barrier.cluster.wait.aligned;" ::: "memory");
            const uint32_t o = SM_XQ + (8 * r + warp) * 256 + (4 * l7 + (lane >> 3)) * 8;
            const uint32_t smo = mapa(sm, r);
            st_async2(smp + o, __float_as_uint(k2[0]), __float_as_uint(k2[1]), smp + SM_BAR + 8 * B_XQ);
            st_async2(smo + o, __float_as_uint(k2[0]), __float_as_uint(k2[1]), smo + SM_BAR + 8 * B_XQ);
        }
        bar_sync(1, 288);
        const unsigned tag = lds32(sm + SM_G + 4);
        {
            mbar_wait(sm + SM_BAR + 8 * B_XQ);
            float2 qv[16];
#pragma unroll
            for (int i = 0; i < 16; i++) qv[i] = lds64f(sm + SM_XQ + i * 256 + lane * 8);
#pragma unroll
            for (int i = 0; i < 8; i++) { qv[i].x += qv[i + 8].x; qv[i].y += qv[i + 8].y; }
#pragma unroll
            for (int i = 0; i < 4; i++) { qv[i].x += qv[i + 4].x; qv[i].y += qv[i + 4].y; }
            qv[0].x = (qv[0].x + qv[2].x) + (qv[1].x + qv[3].x);
            qv[0].y = (qv[0].y + qv[2].y) + (qv[1].y + qv[3].y);
            const uint32_t qw = pack_bf16(qv[0].x, qv[0].y);
            uint32_t qb[8];
#pragma unroll
            for (int i = 0; i < 8; i++) qb[i] = __shfl_sync(0xffffffffu, qw, 4 * i + t);
            STAMP(1);
            mbar_wait(sm + SM_BAR + 8 * (B_WUK + kq));
            STAMP_T(224, 20);
            uint32_t a[8][4];
#pragma unroll
            for (int s = 0; s < 8; s++) ldsm4((a_wuk ^ ((s & 3) << 5)) + (s >> 2) * 2048, a[s]);
            float c[4][4];
#pragma unroll
            for (int i = 0; i < 4; i++) {
                c[i][0] = c[i][1] = c[i][2] = c[i][3] = 0.f;
                mma4(c[i], a[2 * i], qb[4 * (i & 1)], qb[4 * (i & 1) + 1]);
            }
#pragma unroll
            for (int i = 0; i < 4; i++) mma4(c[i], a[2 * i + 1], qb[4 * (i & 1) + 2], qb[4 * (i & 1) + 3]);
            const float sc = 0.08838834764831845f * 1.4426950408889634f;
            const float lo = ((t & 1) ? c[2][0] + c[3][0] : c[0][0] + c[1][0]) * sc;
            const float hi = ((t & 1) ? c[2][2] + c[3][2] : c[0][2] + c[1][2]) * sc;
            const uint32_t lob = (lo != lo) ? 0x7FFEu : (((__float_as_uint(lo) + 0x10000u) >> 16) & 0xFFFEu);
            if (t < 2) st_pub1(p_e2w, (pack_bf16(0.f, hi) & 0xFFFF0000u) | lob | tag);
        }
        STAMP_T(224, 2);
        {
            bar_sync(3, 256);
            float s[4][4];
#pragma unroll
            for (int i = 0; i < 4; i++) s[i][0] = s[i][1] = s[i][2] = s[i][3] = 0.f;
            uint32_t ct[4][4][4];
            uint32_t bf[2][4][4];
            uint4 v[4];
#define LOAD_BF(q) _Pragma("unroll") for (int i = 0; i < 4; i++) ldsm4((a_s ^ ((i >> 1) << 6)) + (q) * 16384 + (i & 1) * 1024, bf[(q) & 1][i])
#define LOAD_CT()  _Pragma("unroll") for (int i = 0; i < 16; i++) ldsm4t((a_ct ^ ((i >> 2) << 4)) + (i & 3) * 4096, ct[i >> 2][i & 3])
#define STAGE_Q(st2) do { \
                int it = 0; \
                while ((chk4(chk4(0u, v[2 * (st2)], tag), v[2 * (st2) + 1], tag) & 1u) && ++it < SPIN_MAX) { \
                    v[2 * (st2)] = ld_poll4(p_e2r + (st2) * 16); \
                    v[2 * (st2) + 1] = ld_poll4(p_e2r + (st2) * 16 + 2048); \
                } \
                PROF_ROUNDS(st2 ? 28 : 18, it); \
                const uint4 &x = v[2 * (st2)], &y = v[2 * (st2) + 1]; \
                sts128u(a_qsw + (st2) * 256, add_bf16x2(x.x, y.x), add_bf16x2(x.y, y.y), add_bf16x2(x.z, y.z), add_bf16x2(x.w, y.w)); \
                if (st2 == 0) { v[2] = ld_poll4(p_e2r + 16); v[3] = ld_poll4(p_e2r + 16 + 2048); } \
                bar_sync(3, 256); \
            } while (0)
#define LOAD_QA(q) _Pragma("unroll") for (int i = 0; i < 4; i++) ldsm4((a_qsr ^ (i << 5)) + (q) * 128, qa[(q) & 1][i])
#define S_BLOCK(q) do { \
                const uint32_t (&A)[4][4] = qa[(q) & 1]; const uint32_t (&B)[4][4] = bf[(q) & 1]; \
                mma4(s[0], A[0], B[0][0], B[0][1]); mma4(s[1], A[0], B[1][0], B[1][1]); \
                mma4(s[2], A[1], B[0][2], B[0][3]); mma4(s[3], A[1], B[1][2], B[1][3]); \
                mma4(s[0], A[2], B[2][0], B[2][1]); mma4(s[1], A[2], B[3][0], B[3][1]); \
                mma4(s[2], A[3], B[2][2], B[2][3]); mma4(s[3], A[3], B[3][2], B[3][3]); \
            } while (0)
            uint32_t qa[2][4][4];
            mbar_wait(sm + SM_BAR + 8 * (B_CKV + 0));
            STAMP(19);
            v[0] = ld_poll4(p_e2r);
            v[1] = ld_poll4(p_e2r + 2048);
            LOAD_BF(0);
            mbar_wait(sm + SM_BAR + 8 * (B_CKV + 1));
            LOAD_BF(1);
            if (kq < 2) { LOAD_CT(); }
            STAGE_Q(0);
            STAMP(26);
            LOAD_QA(0);
            LOAD_QA(1);
            S_BLOCK(0);
            S_BLOCK(1);
            mbar_wait(sm + SM_BAR + 8 * (B_CKV + 2));
            LOAD_BF(2);
            if (kq == 2) { LOAD_CT(); }
            STAMP(11);
            STAGE_Q(1);
            STAMP(3);
            LOAD_QA(2);
            LOAD_QA(3);
            mbar_wait(sm + SM_BAR + 8 * (B_CKV + 3));
            STAMP(4);
            LOAD_BF(3);
            S_BLOCK(2);
            S_BLOCK(3);
            {
                const float u0 = s[0][0] + s[2][0], u1 = s[0][1] + s[2][1], u2 = s[1][0] + s[3][0], u3 = s[1][1] + s[3][1];
                const float v0 = s[0][2] + s[2][2], v1 = s[0][3] + s[2][3], v2 = s[1][2] + s[3][2], v3 = s[1][3] + s[3][3];
                st_async4(smp + SM_SPR + o_spw, u0, u1, u2, u3, smp + SM_BAR + 8 * B_SP);
                st_async4(smp + SM_SPR + 512 + o_spw, v0, v1, v2, v3, smp + SM_BAR + 8 * B_SP);
                sts128(sm + SM_SPL + o_spw, u0, u1, u2, u3);
                sts128(sm + SM_SPL + 512 + o_spw, v0, v1, v2, v3);
            }
            if (kq == 3) { LOAD_CT(); }
            bar_sync(3, 256);
            STAMP(5);
            {
                const uint4 ul = lds128(a_sr + SM_SPL), vl = lds128(a_sr + SM_SPL + 512);
                mbar_wait(sm + SM_BAR + 8 * B_SP);
                STAMP(6);
                const uint4 ur = lds128(a_sr + SM_SPR), vr = lds128(a_sr + SM_SPR + 512);
                const float u0 = __uint_as_float(ul.x) + __uint_as_float(ur.x), u1 = __uint_as_float(ul.y) + __uint_as_float(ur.y);
                const float u2 = __uint_as_float(ul.z) + __uint_as_float(ur.z), u3 = __uint_as_float(ul.w) + __uint_as_float(ur.w);
                const float v0 = __uint_as_float(vl.x) + __uint_as_float(vr.x), v1 = __uint_as_float(vl.y) + __uint_as_float(vr.y);
                const float v2 = __uint_as_float(vl.z) + __uint_as_float(vr.z), v3 = __uint_as_float(vl.w) + __uint_as_float(vr.w);
                const float mu = warp_max(fmaxf(fmaxf(u0, u1), fmaxf(u2, u3)));
                const float mv = warp_max(fmaxf(fmaxf(v0, v1), fmaxf(v2, v3)));
                const uint32_t a0 = pack_bf16(ex2(u0 - mu), ex2(u1 - mu)), a2 = pack_bf16(ex2(u2 - mu), ex2(u3 - mu));
                const uint32_t a1 = pack_bf16(ex2(v0 - mv), ex2(v1 - mv)), a3 = pack_bf16(ex2(v2 - mv), ex2(v3 - mv));
                sts128u(sm + SM_P + g * 512 + warp * 64 + t * 16, a0, a1, a2, a3);
                bar_sync(3, 256);
                STAMP(7);
                uint4 pa[8];
#pragma unroll
                for (int q = 0; q < 8; q++) pa[q] = lds128(sm + SM_P + q * 512 + lane * 16);
                float o[2][4][4];
#pragma unroll
                for (int n = 0; n < 4; n++)
#pragma unroll
                    for (int e = 0; e < 4; e++) o[0][n][e] = o[1][n][e] = 0.f;
#pragma unroll
                for (int i = 0; i < 4; i++) {
#pragma unroll
                    for (int n = 0; n < 4; n++) mma(o[0][n], pa[2 * i].x, pa[2 * i].y, pa[2 * i].z, pa[2 * i].w, ct[n][i][0], ct[n][i][1]);
#pragma unroll
                    for (int n = 0; n < 4; n++) mma(o[1][n], pa[2 * i + 1].x, pa[2 * i + 1].y, pa[2 * i + 1].z, pa[2 * i + 1].w, ct[n][i][2], ct[n][i][3]);
                }
                const uint32_t q0 = r ? a1 : a0, q1 = r ? a3 : a2;
                float l = (bf_lo(q0) + bf_hi(q0)) + (bf_lo(q1) + bf_hi(q1));
#pragma unroll
                for (int d = 1; d < 32; d <<= 1) l += shfl_x(l, d);
                if (lane < STS_) st_pub64(p_stw, tagf(l, tag), __float_as_uint(r ? mv : mu));
                uint32_t w0[4], w1[4];
#pragma unroll
                for (int n = 0; n < 4; n++) {
                    w0[n] = pack_bf16(o[0][n][0] + o[1][n][0], o[0][n][1] + o[1][n][1]);
                    w1[n] = pack_bf16(o[0][n][2] + o[1][n][2], o[0][n][3] + o[1][n][3]);
                }
                st_pub2x64(p_e3w, tagw(w0[0], tag), w0[1], tagw(w0[2], tag), w0[3]);
                st_pub2x64(p_e3w + 8 * 2 * 8 * 32 * 4, tagw(w1[0], tag), w1[1], tagw(w1[2], tag), w1[3]);
            }
        }
        const unsigned t_e3 = clock32() + D3;
        STAMP(8);
        if (ffn) {
            const uint32_t xa = sm + SM_XS + 160 * kq + 4 * t;
            uint32_t xb[5][2];
#pragma unroll
            for (int s = 0; s < 5; s++) { xb[s][0] = lds32(xa + s * 32); xb[s][1] = lds32(xa + s * 32 + 16); }
            mbar_wait(sm + SM_BAR + 8 * (B_W1 + (warp >> 2)));
            uint32_t a[5][4];
#pragma unroll
            for (int s = 0; s < 5; s++) ldsm4t(a_w1 + s * 1024, a[s]);
            float c0[4] = {0.f, 0.f, 0.f, 0.f}, c1[4] = {0.f, 0.f, 0.f, 0.f};
#pragma unroll
            for (int s = 0; s < 5; s++) mma4((s & 1) ? c1 : c0, a[s], xb[s][0], xb[s][1]);
            if (t < 2) st_async1(a_xh, t ? c0[2] + c1[2] : c0[0] + c1[0], b_xh + SM_BAR + 8 * B_XH);
        }
        STAMP(9);
        float invl;
        {
            uint32_t a[8][4];
            mbar_wait(sm + SM_BAR + 8 * (B_WUV + kq));
#pragma unroll
            for (int i = 0; i < 8; i++) ldsm4t((a_wuv ^ ((i >> 1) << 5)) + (i & 1) * 2048, a[i]);
            uint4 v[4];
            uint32_t fw[4];
            int it = 0;
            spin_until(t_e3);
            STAMP(24);
            uint2 st = ld_poll64(p_str);
#pragma unroll
            for (int i = 0; i < 4; i++) v[i] = ld_poll2x64(p_e3r + i * 32);
            while (((st.x ^ tag) & 1u) && ++it < SPIN_MAX) st = ld_poll64(p_str);
            __syncwarp();
            {
                const float M = warp_max(__uint_as_float(st.y));
                const float ff = ex2(__uint_as_float(st.y) - M);
                const uint32_t f2 = pack_bf16(ff, ff);
                float L = bf_lo(f2) * untagf(st.x);
#pragma unroll
                for (int i = 0; i < 4; i++) fw[i] = __shfl_sync(0xffffffffu, f2, 8 * i + g);
#pragma unroll
                for (int d = 1; d < 32; d <<= 1) L += shfl_x(L, d);
                invl = __fdividef(1.f, L);
            }
            while (true) {
                unsigned bad = 0u;
#pragma unroll
                for (int i = 0; i < 4; i++) bad = chk(chk(bad, v[i].x, tag), v[i].z, tag);
                if (!(bad & 1u) || ++it >= SPIN_MAX) break;
#pragma unroll
                for (int i = 0; i < 4; i++) v[i] = ld_poll2x64(p_e3r + i * 32);
            }
            PROF_ROUNDS(25, it);
            __syncwarp();
            STAMP(10);
            uint32_t bx = mul_bf16x2(fw[0], v[0].x & ~1u), by = mul_bf16x2(fw[0], v[0].y), bz = mul_bf16x2(fw[0], v[0].z & ~1u), bw = mul_bf16x2(fw[0], v[0].w);
#pragma unroll
            for (int i = 1; i < 4; i++) {
                bx = fma_bf16x2(fw[i], v[i].x & ~1u, bx); by = fma_bf16x2(fw[i], v[i].y, by);
                bz = fma_bf16x2(fw[i], v[i].z & ~1u, bz); bw = fma_bf16x2(fw[i], v[i].w, bw);
            }
            float c[4][4];
#pragma unroll
            for (int i = 0; i < 4; i++) {
                c[i][0] = c[i][1] = c[i][2] = c[i][3] = 0.f;
                mma4(c[i], a[2 * i], bx, by);
            }
#pragma unroll
            for (int i = 0; i < 4; i++) mma4(c[i], a[2 * i + 1], bz, bw);
            float e[8], k4[4];
#pragma unroll
            for (int i = 0; i < 4; i++) { e[2 * i] = c[i][0] + c[i][1]; e[2 * i + 1] = c[i][2] + c[i][3]; }
            const bool t1 = t & 2, t0 = t & 1;
#pragma unroll
            for (int i = 0; i < 4; i++) k4[i] = (t1 ? e[4 + i] : e[i]) + shfl_x(t1 ? e[i] : e[4 + i], 2);
            const float k0 = (t0 ? k4[2] : k4[0]) + shfl_x(t0 ? k4[0] : k4[2], 1);
            const float k1 = (t0 ? k4[3] : k4[1]) + shfl_x(t0 ? k4[1] : k4[3], 1);
            st_async2(a_xc, __float_as_uint(k0), __float_as_uint(k1), b_xc + SM_BAR + 8 * B_XC);
        }
        STAMP(12);
        {
            float c[5][4];
#pragma unroll
            for (int i = 0; i < 5; i++) c[i][0] = c[i][1] = c[i][2] = c[i][3] = 0.f;
            const int half = warp >> 2;
            const float gt = __uint_as_float(lds32(sm + SM_G));
            if (ffn) {
                mbar_wait(sm + SM_BAR + 8 * B_XH);
                const uint4 u = lds128(sm + SM_XH + (lane & 15) * 32), v = lds128(sm + SM_XH + (lane & 15) * 32 + 16);
                float hv = ((__uint_as_float(u.x) + __uint_as_float(u.y)) + (__uint_as_float(u.z) + __uint_as_float(u.w))) +
                           ((__uint_as_float(v.x) + __uint_as_float(v.y)) + (__uint_as_float(v.z) + __uint_as_float(v.w)));
                hv = bf_lo(pack_bf16(hv, 0.f));
                hv = __fdividef(hv, 1.f + __expf(-hv)) * (1.f - gt);
                const uint32_t w = pack_bf16(hv, shfl_x(hv, 1));
                const uint32_t b0 = __shfl_sync(0xffffffffu, w, 2 * t), b1 = __shfl_sync(0xffffffffu, w, 8 + 2 * t);
                mbar_wait(sm + SM_BAR + 8 * (B_W2 + half));
                uint32_t a[5][4];
#pragma unroll
                for (int i = 0; i < 5; i++) ldsm4t(a_fin[i] + SM_W2, a[i]);
#pragma unroll
                for (int i = 0; i < 5; i++) mma4(c[i], a[i], b0, b1);
            }
            uint32_t wa[2][5][4];
            mbar_wait(sm + SM_BAR + 8 * (B_WO + half));
#pragma unroll
            for (int i = 0; i < 5; i++) ldsm4t(a_fin[i] + SM_WO, wa[0][i]);
            const bool early = mbar_test(sm + SM_BAR + 8 * (B_WO + 2 + half));
            if (early) {
#pragma unroll
                for (int i = 0; i < 5; i++) ldsm4t(a_fin[i] + SM_WO + 20480, wa[1][i]);
            }
            mbar_wait(sm + SM_BAR + 8 * B_XC);
            STAMP(13);
            float xv[16];
#pragma unroll
            for (int i = 0; i < 16; i++) xv[i] = __uint_as_float(lds32(sm + SM_XC + i * 128 + lane * 4));
#pragma unroll
            for (int i = 0; i < 8; i++) xv[i] += xv[i + 8];
            const float cv = (((xv[0] + xv[4]) + (xv[1] + xv[5])) + ((xv[2] + xv[6]) + (xv[3] + xv[7]))) * (gt * invl);
            const uint32_t w = pack_bf16(cv, shfl_x(cv, 2));
            uint32_t bb[4];
#pragma unroll
            for (int q = 0; q < 4; q++) bb[q] = __shfl_sync(0xffffffffu, w, (q >> 1) * 16 + 4 * t + (q & 1));
#pragma unroll
            for (int i = 0; i < 5; i++) mma4(c[i], wa[0][i], bb[0], bb[1]);
            if (!early) {
                mbar_wait(sm + SM_BAR + 8 * (B_WO + 2 + half));
#pragma unroll
                for (int i = 0; i < 5; i++) ldsm4t(a_fin[i] + SM_WO + 20480, wa[1][i]);
            }
#pragma unroll
            for (int i = 0; i < 5; i++) mma4(c[i], wa[1][i], bb[2], bb[3]);
            STAMP_T(224, 14);
            const bool t0 = t & 1, t1 = t & 2;
            const float v0 = t1 ? (t0 ? c[1][2] : c[1][0]) : (t0 ? c[0][2] : c[0][0]);
            const float v1 = t1 ? (t0 ? c[3][2] : c[3][0]) : (t0 ? c[2][2] : c[2][0]);
            const float v2 = t0 ? c[4][2] : c[4][0];
            st_pub1(p_e4w, tagf(v0, tag));
            st_pub1(p_e4w + 4 * NCTA * 8, tagf(v1, tag));
            if (!t1) st_pub1(p_e4w + 8 * NCTA * 8, tagf(v2, tag));
        }
        STAMP_T(224, 15);
        if (b < 80) {
            const uint4* p = S->e4 + b * NCTA * 2 + tid;
            spin_until(clock32() + D4);
            uint4 v;
            int it = 0;
            do { v = ld_poll4(p); } while ((chk4(0u, v, tag) & 1u) && ++it < SPIN_MAX);
            __syncwarp();
            STAMP(16);
            const bool b4 = lane & 16, b3 = lane & 8;
            const float k0 = untagf(b4 ? v.z : v.x) + shfl_x(untagf(b4 ? v.x : v.z), 16);
            const float k1 = untagf(b4 ? v.w : v.y) + shfl_x(untagf(b4 ? v.y : v.w), 16);
            float s = (b3 ? k1 : k0) + shfl_x(b3 ? k0 : k1, 8);
            s += shfl_x(s, 4);
            s += shfl_x(s, 2);
            if (!(lane & 6)) sts32(sm + SM_FIN + ((lane & 1) * 4 + (lane >> 3)) * 32 + warp * 4, __float_as_uint(s));
            bar_sync(3, 256);
            if (tid < 8) {
                const uint4 u = lds128(sm + SM_FIN + tid * 32), w = lds128(sm + SM_FIN + tid * 32 + 16);
                P.out[b * 8 + tid] = __float2bfloat16(((__uint_as_float(u.x) + __uint_as_float(u.y)) + (__uint_as_float(u.z) + __uint_as_float(u.w))) +
                                                      ((__uint_as_float(w.x) + __uint_as_float(w.y)) + (__uint_as_float(w.z) + __uint_as_float(w.w))));
                if (b == 0 && tid == 0) st_pub1(&S->epoch, tag);
            }
            STAMP(17);
        }
    } else if (warp == 8) {
        const unsigned t0 = gtimer();
        const uint32_t bar = sm + SM_BAR + 8 * lane;
        if (lane == 0) {
#pragma unroll
            for (int i = 0; i < NBAR; i++) asm volatile("mbarrier.init.shared::cta.b64 [%0], 1;" :: "r"(sm + SM_BAR + 8 * i) : "memory");
            asm volatile("mbarrier.arrive.expect_tx.shared::cta.b64 _, [%0], 8192;" :: "r"(sm + SM_BAR + 8 * B_SP) : "memory");
            asm volatile("mbarrier.arrive.expect_tx.shared::cta.b64 _, [%0], 2048;" :: "r"(sm + SM_BAR + 8 * B_XC) : "memory");
            asm volatile("mbarrier.arrive.expect_tx.shared::cta.b64 _, [%0], 512;" :: "r"(sm + SM_BAR + 8 * B_XH) : "memory");
            asm volatile("mbarrier.arrive.expect_tx.shared::cta.b64 _, [%0], 4096;" :: "r"(sm + SM_BAR + 8 * B_XQ) : "memory");
            asm volatile("fence.mbarrier_init.release.cluster;" ::: "memory");
        }
        __syncwarp();
        asm volatile("barrier.cluster.arrive.relaxed.aligned;" ::: "memory");
        if (lane < 6) asm volatile("prefetch.tensormap [%0];" :: "l"(&P.m[lane]) : "memory");
        float warm[4] = {0.f, 0.f, 0.f, 0.f};
        {
            int map, c0 = 0, c1, c2;
            uint32_t dst, bytes, due;
            const int k = lane;
            constexpr int DF = DT_NS * 135 / 128;
            if (k < B_CKV)      { map = 0; c1 = 256 * r + 64 * k;            c2 = 2 * h + pp;         dst = SM_WUK + k * 8192;            bytes = 8192;  due = k * DT_NS; }
            else if (k < B_W1)  { map = 1; c1 = 128 * h;                     c2 = 4 * r + k - B_CKV;  dst = SM_CKV + (k - B_CKV) * 16384; bytes = 16384; due = k * DT_NS; }
            else if (k < B_WUV) { map = 2; c1 = 320 * r + 160 * (k - B_W1);  c2 = h; c0 = 32 * pp;    dst = SM_W1 + (k - B_W1) * 10240;   bytes = ffn ? 10240 : 0; due = 8 * DT_NS + (k - B_W1) * DF; }
            else if (k < B_W2)  { map = 3; c1 = 256 * r + 64 * (k - B_WUV);  c2 = 2 * h + pp;         dst = SM_WUV + (k - B_WUV) * 8192;  bytes = 8192;  due = (k - 2) * DT_NS + 2 * DF; }
            else if (k < B_WO)  { map = 4; c1 = 16 * b;                      c2 = 5 * (k - B_W2);     dst = SM_W2 + (k - B_W2) * 10240;   bytes = ffn ? 10240 : 0; due = 12 * DT_NS + 2 * DF + (k - B_W2) * (DT2_NS * 135 / 128); }
            else                { map = 5; c1 = 32 * b + 16 * ((k - B_WO) >> 1); c2 = 5 * (k & 1);    dst = SM_WO + (k - B_WO) * 10240;   bytes = k < B_SP ? 10240 : 0;
                                  due = 12 * DT_NS + 2 * DF + 2 * (DT2_NS * 135 / 128) + (k - B_WO) * (DT2_NS * 5 / 4); }
            due += T0_NS;
            {
                constexpr int gap[20] = SCHED;
                due = 0;
#pragma unroll
                for (int i = 0; i < 20; i++) due += (i <= k) ? gap[i] : 0;
                due += ((b * 37) & 127) * (k < 4 ? STAG_A : STAG_B) / 128;
            }
            bool pending = bytes != 0;
            if (pending) asm volatile("mbarrier.arrive.expect_tx.shared::cta.b64 _, [%0], %1;" :: "r"(bar), "r"(bytes) : "memory");
            STAMP_T(256, 21);
            while (__any_sync(0xffffffffu, pending)) {
                const unsigned now = gtimer() - t0;
                if (pending && now >= due) {
                    asm volatile("cp.async.bulk.tensor.3d.shared::cluster.global.mbarrier::complete_tx::bytes [%0], [%1, {%3,%4,%5}], [%2];"
                                 :: "r"(sm + dst), "l"(&P.m[map]), "r"(bar), "r"(c0), "r"(c1), "r"(c2) : "memory");
                    pending = false;
                }
            }
        }
        if (lane >= B_W2 && lane < B_SP && (ffn || lane >= B_WO)) mbar_wait(bar);
        STAMP_T(256, 22);
    } else {
        const unsigned old = ld_poll1(&S->epoch) & 1u;
        uint32_t xv[10], gw[10];
#pragma unroll
        for (int i = 0; i < 10; i++) {
            xv[i] = ldg32(P.x + (i * 32 + lane) * 2);
            gw[i] = ldg32(P.gate + (i * 32 + lane) * 2);
        }
        asm volatile("barrier.cluster.arrive.relaxed.aligned;" ::: "memory");
        st_pub4(S->e2 + (pp * 32 + h) * 64 + 32 * r + lane, old, old, old, old);
        if ((lane & 3) < STS_) st_pub64(S->st + ((16 * pp + 8 * r + (lane >> 2)) * 32 + h) * STS_ + (lane & 3), old, 0u);
        if (lane == 0) sts32(sm + SM_G + 4, old ^ 1u);
#pragma unroll
        for (int i = 0; i < 5; i++) st_pub4(&S->e4[((i * 16 + (lane >> 1)) * NCTA + b) * 2 + (lane & 1)], old, old, old, old);
        float z = 0.f;
#pragma unroll
        for (int i = 0; i < 10; i++) {
            if ((i >= 5) == (r != 0)) sts32(sm + SM_XS + ((i % 5) * 32 + lane) * 4, xv[i]);
            z = fmaf(bf_lo(xv[i]), bf_lo(gw[i]), z);
            z = fmaf(bf_hi(xv[i]), bf_hi(gw[i]), z);
        }
#pragma unroll
        for (int d = 1; d < 32; d <<= 1) z += shfl_x(z, d);
        if (lane == 0) sts32(sm + SM_G, __float_as_uint(__fdividef(1.f, 1.f + __expf(-z))));
        bar_arrive(1, 288);
    }
}

typedef CUresult (*EncodeFn)(CUtensorMap*, CUtensorMapDataType, cuuint32_t, void*, const cuuint64_t*, const cuuint64_t*,
                             const cuuint32_t*, const cuuint32_t*, CUtensorMapInterleave, CUtensorMapSwizzle,
                             CUtensorMapL2promotion, CUtensorMapFloatOOBfill);

void make_map(EncodeFn enc, CUtensorMap* m, const void* base, int rows, int cols, int box_cols, int box_rows, int box_blks) {
    cuuint64_t gd[3] = {64, (cuuint64_t)rows, (cuuint64_t)(cols / 64)};
    cuuint64_t gs[2] = {(cuuint64_t)cols * 2, 128};
    cuuint32_t bd[3] = {(cuuint32_t)box_cols, (cuuint32_t)box_rows, (cuuint32_t)box_blks};
    cuuint32_t es[3] = {1, 1, 1};
    enc(m, CU_TENSOR_MAP_DATA_TYPE_BFLOAT16, 3, const_cast<void*>(base), gd, gs, bd, es, CU_TENSOR_MAP_INTERLEAVE_NONE,
        box_cols == 64 ? CU_TENSOR_MAP_SWIZZLE_128B : CU_TENSOR_MAP_SWIZZLE_64B,
        box_cols == 64 ? CU_TENSOR_MAP_L2_PROMOTION_NONE : CU_TENSOR_MAP_L2_PROMOTION_L2_128B, CU_TENSOR_MAP_FLOAT_OOB_FILL_NONE);
}

}

extern "C" void kernel_launch(void* const* d_in, const int* in_sizes, int n_in, void* d_out, int out_size) {
    (void)in_sizes; (void)n_in; (void)out_size;
    constexpr int smem_bytes = SMEM_BYTES;
    static EncodeFn enc = nullptr;
    static Scratch* scratch = nullptr;
    if (!enc) {
        void* fn = nullptr;
        cudaDriverEntryPointQueryResult st;
        cudaGetDriverEntryPoint("cuTensorMapEncodeTiled", &fn, cudaEnableDefault, &st);
        enc = (EncodeFn)fn;
        cudaFuncSetAttribute(fused_kernel, cudaFuncAttributeMaxDynamicSharedMemorySize, smem_bytes);
        cudaGetSymbolAddress((void**)&scratch, g_s);
    }
    Params p;
    make_map(enc, &p.m[0], d_in[3], 512, 4096, 64, 64, 1);
    make_map(enc, &p.m[1], d_in[1], 4096, 512, 64, 128, 1);
    make_map(enc, &p.m[2], d_in[7], 640, 1728, 32, 160, 1);
    make_map(enc, &p.m[3], d_in[4], 512, 4096, 64, 64, 1);
    make_map(enc, &p.m[4], d_in[8], 1728, 640, 64, 16, 5);
    make_map(enc, &p.m[5], d_in[5], 4096, 640, 64, 16, 5);
    p.x = (const __nv_bfloat16*)d_in[0];
    p.wq = (const __nv_bfloat16*)d_in[2];
    p.gate = (const __nv_bfloat16*)d_in[9];
    p.out = (__nv_bfloat16*)d_out;
    p.s = scratch;
    fused_kernel<<<NCTA, NTHREADS, smem_bytes>>>(p);
}
```

```cpp
#include <cuda_runtime.h>
#include <cuda.h>
#include <cuda_bf16.h>
#include <stdint.h>

namespace {

constexpr int NCTA = 128;
constexpr int NTHREADS = 320;
constexpr int SPIN_MAX = 1 << 18;

constexpr int SM_WUK = 0;
constexpr int SM_CKV = SM_WUK + 32768;
constexpr int SM_WUV = SM_CKV + 65536;
constexpr int SM_W1  = SM_WUV + 32768;
constexpr int SM_W2  = SM_W1 + 20480;
constexpr int SM_WO  = SM_W2 + 20480;
constexpr int SM_SPR = SM_WO + 40960;
constexpr int SM_QS  = SM_WUK;
constexpr int SM_SPL = SM_WUK + 8192;
constexpr int SM_P   = SM_WUK + 16384;
constexpr int SM_FIN = SM_WUK + 24576;
constexpr int SM_XQ  = SM_SPR + 8192;
constexpr int SM_XS  = SM_XQ + 4096;
constexpr int SM_XC  = SM_XS + 640;
constexpr int SM_XH  = SM_XC + 2048;
constexpr int SM_G   = SM_XH + 512;
constexpr int SM_F   = SM_G + 32;
constexpr int SM_BAR = SM_F + 128;
constexpr int SM_END = SM_BAR + 32 * 8;
constexpr int SMEM_BYTES = SM_END;
static_assert(SMEM_BYTES <= 232448 - 256, "smem");

constexpr int B_WUK = 0, B_CKV = 4, B_W1 = 8, B_WUV = 10, B_W2 = 14, B_WO = 16, B_SP = 20, B_XC = 21, B_XH = 22, B_XQ = 23, NBAR = 24;

struct Scratch {
    uint4    e3[32 * 2 * 8 * 32 * 4];
    uint4    e4[80 * NCTA * 2];
    uint4    e2[2 * 32 * 64];
    uint2    st[32 * 32 * 16];
    unsigned epoch;
};
__device__ __align__(1024) Scratch g_s;

struct Params {
    const __nv_bfloat16* wq;
    const __nv_bfloat16* x;
    Scratch* s;
    const __nv_bfloat16* gate;
    __nv_bfloat16* out;
    alignas(64) CUtensorMap m[7];
};

#define STAMP(i)
#define STAMP_T(t, i)

__device__ __forceinline__ unsigned clock32() { unsigned c; asm volatile("mov.u32 %0, %%clock;" : "=r"(c) :: "memory"); return c; }
__device__ __forceinline__ unsigned gtimer() { unsigned c; asm volatile("mov.u32 %0, %%globaltimer_lo;" : "=r"(c) :: "memory"); return c; }

__device__ __forceinline__ uint4 ldg_stream(const void* p) {
    uint4 v;
    asm volatile("ld.global.nc.L1::no_allocate.v4.u32 {%0,%1,%2,%3}, [%4];"
                 : "=r"(v.x), "=r"(v.y), "=r"(v.z), "=r"(v.w) : "l"(p));
    return v;
}
__device__ __forceinline__ uint4 ld_poll4(const void* p) {
    uint4 v;
    asm volatile("ld.relaxed.gpu.global.v4.u32 {%0,%1,%2,%3}, [%4];"
                 : "=r"(v.x), "=r"(v.y), "=r"(v.z), "=r"(v.w) : "l"(p) : "memory");
    return v;
}
__device__ __forceinline__ uint4 ld_poll2x64(const void* p) {
    uint4 v;
    asm volatile("{.reg .b64 a, b; ld.relaxed.gpu.global.v2.b64 {a, b}, [%4]; mov.b64 {%0,%1}, a; mov.b64 {%2,%3}, b;}"
                 : "=r"(v.x), "=r"(v.y), "=r"(v.z), "=r"(v.w) : "l"(p) : "memory");
    return v;
}
__device__ __forceinline__ uint2 ld_poll64(const void* p) {
    uint2 v;
    asm volatile("{.reg .b64 a; ld.relaxed.gpu.global.b64 a, [%2]; mov.b64 {%0,%1}, a;}" : "=r"(v.x), "=r"(v.y) : "l"(p) : "memory");
    return v;
}
__device__ __forceinline__ unsigned ld_poll1(const void* p) {
    unsigned v;
    asm volatile("ld.relaxed.gpu.global.u32 %0, [%1];" : "=r"(v) : "l"(p) : "memory");
    return v;
}
__device__ __forceinline__ void st_pub2x64(void* p, unsigned a, unsigned b, unsigned c, unsigned d) {
    asm volatile("{.reg .b64 x, y; mov.b64 x, {%1,%2}; mov.b64 y, {%3,%4}; st.relaxed.gpu.global.v2.b64 [%0], {x, y};}"
                 :: "l"(p), "r"(a), "r"(b), "r"(c), "r"(d) : "memory");
}
__device__ __forceinline__ void st_pub64(void* p, unsigned a, unsigned b) {
    asm volatile("{.reg .b64 x; mov.b64 x, {%1,%2}; st.relaxed.gpu.global.b64 [%0], x;}" :: "l"(p), "r"(a), "r"(b) : "memory");
}
__device__ __forceinline__ void st_pub1(void* p, unsigned a) {
    asm volatile("st.relaxed.gpu.global.u32 [%0], %1;" :: "l"(p), "r"(a) : "memory");
}
__device__ __forceinline__ unsigned tagw(unsigned w, unsigned tag) { return (w & ~1u) | tag; }
__device__ __forceinline__ unsigned tagf(float v, unsigned tag) { return (__float_as_uint(v) & ~1u) | tag; }
__device__ __forceinline__ float untagf(unsigned w) { return __uint_as_float(w & ~1u); }

__device__ __forceinline__ void mbar_wait(uint32_t bar) {
    uint32_t ok;
    int it = 0;
#pragma unroll 1
    do {
        asm volatile("{.reg .pred p; mbarrier.try_wait.parity.shared::cta.b64 p, [%1], 0; selp.u32 %0,1,0,p;}"
                     : "=r"(ok) : "r"(bar) : "memory");
    } while (!ok && ++it < SPIN_MAX);
}
__device__ __forceinline__ void bar_sync(int id, int n) { asm volatile("bar.sync %0, %1;" :: "r"(id), "r"(n) : "memory"); }
__device__ __forceinline__ void bar_arrive(int id, int n) { asm volatile("bar.arrive %0, %1;" :: "r"(id), "r"(n) : "memory"); }
__device__ __forceinline__ uint32_t mapa(uint32_t a, uint32_t rank) {
    uint32_t r;
    asm("mapa.shared::cluster.u32 %0, %1, %2;" : "=r"(r) : "r"(a), "r"(rank));
    return r;
}
__device__ __forceinline__ void st_async4(uint32_t a, float x, float y, float z, float w, uint32_t bar) {
    asm volatile("st.async.weak.shared::cluster.mbarrier::complete_tx::bytes.v4.f32 [%0], {%1,%2,%3,%4}, [%5];"
                 :: "r"(a), "f"(x), "f"(y), "f"(z), "f"(w), "r"(bar) : "memory");
}
__device__ __forceinline__ void st_async2(uint32_t a, uint32_t x, uint32_t y, uint32_t bar) {
    asm volatile("st.async.weak.shared::cluster.mbarrier::complete_tx::bytes.v2.b32 [%0], {%1,%2}, [%3];"
                 :: "r"(a), "r"(x), "r"(y), "r"(bar) : "memory");
}

__device__ __forceinline__ void ldsm4(uint32_t a, uint32_t (&r)[4]) {
    asm volatile("ldmatrix.sync.aligned.m8n8.x4.shared.b16 {%0,%1,%2,%3}, [%4];"
                 : "=r"(r[0]), "=r"(r[1]), "=r"(r[2]), "=r"(r[3]) : "r"(a) : "memory");
}
__device__ __forceinline__ void ldsm4t(uint32_t a, uint32_t (&r)[4]) {
    asm volatile("ldmatrix.sync.aligned.m8n8.x4.trans.shared.b16 {%0,%1,%2,%3}, [%4];"
                 : "=r"(r[0]), "=r"(r[1]), "=r"(r[2]), "=r"(r[3]) : "r"(a) : "memory");
}
__device__ __forceinline__ void mma(float (&c)[4], uint32_t a0, uint32_t a1, uint32_t a2, uint32_t a3, uint32_t b0, uint32_t b1) {
    asm("mma.sync.aligned.m16n8k16.row.col.f32.bf16.bf16.f32 {%0,%1,%2,%3}, {%4,%5,%6,%7}, {%8,%9}, {%0,%1,%2,%3};"
        : "+f"(c[0]), "+f"(c[1]), "+f"(c[2]), "+f"(c[3])
        : "r"(a0), "r"(a1), "r"(a2), "r"(a3), "r"(b0), "r"(b1));
}
__device__ __forceinline__ uint32_t pack_bf16(float lo, float hi) {
    uint32_t r;
    asm("cvt.rn.bf16x2.f32 %0, %1, %2;" : "=r"(r) : "f"(hi), "f"(lo));
    return r;
}
__device__ __forceinline__ float bf_lo(uint32_t w) { return __uint_as_float(w << 16); }
__device__ __forceinline__ float bf_hi(uint32_t w) { return __uint_as_float(w & 0xFFFF0000u); }
__device__ __forceinline__ float ex2(float x) { float y; asm("ex2.approx.ftz.f32 %0, %1;" : "=f"(y) : "f"(x)); return y; }
__device__ __forceinline__ uint4 lds128(uint32_t a) {
    uint4 v;
    asm volatile("ld.shared.v4.u32 {%0,%1,%2,%3}, [%4];" : "=r"(v.x), "=r"(v.y), "=r"(v.z), "=r"(v.w) : "r"(a) : "memory");
    return v;
}
__device__ __forceinline__ float2 lds64f(uint32_t a) {
    float2 v;
    asm volatile("ld.shared.v2.f32 {%0,%1}, [%2];" : "=f"(v.x), "=f"(v.y) : "r"(a) : "memory");
    return v;
}
__device__ __forceinline__ uint32_t lds32(uint32_t a) {
    uint32_t v;
    asm volatile("ld.shared.u32 %0, [%1];" : "=r"(v) : "r"(a) : "memory");
    return v;
}
__device__ __forceinline__ void sts128(uint32_t a, float x, float y, float z, float w) {
    asm volatile("st.shared.v4.f32 [%0], {%1,%2,%3,%4};" :: "r"(a), "f"(x), "f"(y), "f"(z), "f"(w) : "memory");
}
__device__ __forceinline__ void sts64(uint32_t a, uint32_t x, uint32_t y) {
    asm volatile("st.shared.v2.u32 [%0], {%1,%2};" :: "r"(a), "r"(x), "r"(y) : "memory");
}
__device__ __forceinline__ void sts32(uint32_t a, uint32_t x) {
    asm volatile("st.shared.u32 [%0], %1;" :: "r"(a), "r"(x) : "memory");
}
__device__ __forceinline__ void sts16(uint32_t a, uint32_t x) {
    asm volatile("st.shared.u16 [%0], %1;" :: "r"(a), "h"((unsigned short)x) : "memory");
}
__device__ __forceinline__ void fma8(float (&acc)[8], float s, const uint4& v) {
    acc[0] = fmaf(s, bf_lo(v.x), acc[0]); acc[1] = fmaf(s, bf_hi(v.x), acc[1]);
    acc[2] = fmaf(s, bf_lo(v.y), acc[2]); acc[3] = fmaf(s, bf_hi(v.y), acc[3]);
    acc[4] = fmaf(s, bf_lo(v.z), acc[4]); acc[5] = fmaf(s, bf_hi(v.z), acc[5]);
    acc[6] = fmaf(s, bf_lo(v.w), acc[6]); acc[7] = fmaf(s, bf_hi(v.w), acc[7]);
}
__device__ __forceinline__ float warp_max(float v) {
    int k = __float_as_int(v);
    k ^= (k >> 31) & 0x7FFFFFFF;
    asm("redux.sync.max.s32 %0, %0, 0xffffffff;" : "+r"(k));
    k ^= (k >> 31) & 0x7FFFFFFF;
    return __int_as_float(k);
}

__device__ __forceinline__ void st_async1(uint32_t a, float x, uint32_t bar) {
    asm volatile("st.async.weak.shared::cluster.mbarrier::complete_tx::bytes.f32 [%0], %1, [%2];" :: "r"(a), "f"(x), "r"(bar) : "memory");
}
__device__ __forceinline__ void st_pub4(void* p, unsigned a, unsigned b, unsigned c, unsigned d) {
    asm volatile("st.relaxed.gpu.global.v4.u32 [%0], {%1,%2,%3,%4};" :: "l"(p), "r"(a), "r"(b), "r"(c), "r"(d) : "memory");
}
__device__ __forceinline__ uint32_t ldg32(const void* p) {
    uint32_t v;
    asm volatile("ld.global.nc.u32 %0, [%1];" : "=r"(v) : "l"(p));
    return v;
}
__device__ __forceinline__ void mma4(float (&c)[4], const uint32_t (&a)[4], uint32_t b0, uint32_t b1) { mma(c, a[0], a[1], a[2], a[3], b0, b1); }
__device__ __forceinline__ float shfl_x(float v, int m) { return __shfl_xor_sync(0xffffffffu, v, m); }
__device__ __forceinline__ unsigned chk(unsigned acc, unsigned w, unsigned tag) {
    unsigned d;
    asm("lop3.b32 %0, %1, %2, %3, 0xF6;" : "=r"(d) : "r"(acc), "r"(w), "r"(tag));
    return d;
}
__device__ __forceinline__ unsigned chk4(unsigned acc, const uint4& v, unsigned tag) { return chk(chk(chk(chk(acc, v.x, tag), v.y, tag), v.z, tag), v.w, tag); }
__device__ __forceinline__ void sts128u(uint32_t a, uint32_t x, uint32_t y, uint32_t z, uint32_t w) {
    asm volatile("st.shared.v4.u32 [%0], {%1,%2,%3,%4};" :: "r"(a), "r"(x), "r"(y), "r"(z), "r"(w) : "memory");
}
__device__ __forceinline__ uint32_t add_bf16x2(uint32_t a, uint32_t b) {
    uint32_t d;
    asm("add.rn.bf16x2 %0, %1, %2;" : "=r"(d) : "r"(a & ~1u), "r"(b & ~1u));
    return d;
}
__device__ __forceinline__ void spin_until(unsigned t) { while ((int)(clock32() - t) < 0) {} }
__device__ __forceinline__ uint32_t fma_bf16x2(uint32_t a, uint32_t b, uint32_t c) {
    uint32_t d;
    asm("fma.rn.bf16x2 %0, %1, %2, %3;" : "=r"(d) : "r"(a), "r"(b), "r"(c));
    return d;
}
__device__ __forceinline__ uint32_t mul_bf16x2(uint32_t a, uint32_t b) {
    uint32_t d;
    asm("mul.rn.bf16x2 %0, %1, %2;" : "=r"(d) : "r"(a), "r"(b));
    return d;
}
__device__ __forceinline__ bool mbar_test(uint32_t bar) {
    uint32_t ok;
    asm volatile("{.reg .pred p; mbarrier.test_wait.parity.shared::cta.b64 p, [%1], 0; selp.u32 %0,1,0,p;}" : "=r"(ok) : "r"(bar) : "memory");
    return __all_sync(0xffffffffu, ok);
}
__device__ __forceinline__ uint4 ld_home4(const void* p) {
    uint4 v;
    asm volatile("{.reg .b128 d, z; .reg .b64 lo, hi; mov.b64 lo, 0; mov.b128 z, {lo, lo};"
                 " atom.relaxed.gpu.global.cas.b128 d, [%4], z, z; mov.b128 {lo, hi}, d; mov.b64 {%0,%1}, lo; mov.b64 {%2,%3}, hi;}"
                 : "=r"(v.x), "=r"(v.y), "=r"(v.z), "=r"(v.w) : "l"(p) : "memory");
    return v;
}
#define PIN(x) asm volatile("" : "+r"(x))
#define PINL(x) asm volatile("" : "+l"(x))

#define SCHED {1440, 225, 279, 159, 537, 340, 400, 338, 308, 240, 474, 49, 370, 419, 198, 410, 463, 393, 459, 355}
#define STAG_A 265
#define STAG_B 345
#define D3 1450
#define D4 400
#define D5 200
#define D6 0
#define TA_NS 4000
#define TB_NS 4350
#define STS_ 4
#define T0_NS 1400
#define DT_NS 325
#define QGATE_A 0
#define QGATE_B 2
#define CT_EARLY 0
#define DS 700
#define PROF_ROUNDS(k, it)
#define CTE 2
#define POLL 1
#define E4MODE 0
#define DT2_NS DT_NS

__global__ void __cluster_dims__(2, 1, 1) __launch_bounds__(NTHREADS, 1)
fused_kernel(const __grid_constant__ Params P)
{
    extern __shared__ __align__(1024) unsigned char smem_raw[];
    const int tid = threadIdx.x;
    const int cl = blockIdx.x >> 1;
    const int r = blockIdx.x & 1;
    const uint32_t sm = (uint32_t)__cvta_generic_to_shared(smem_raw);
    uint4 wv[10];
    uint32_t xw[5];
    if (tid < 256) {
        asm volatile("barrier.cluster.arrive.relaxed.aligned;" ::: "memory");
        const int m0 = 320 * r + 10 * (tid >> 3);
        const __nv_bfloat16* wp = P.wq + (size_t)m0 * 4096 + cl * 64 + (tid & 7) * 8;
#pragma unroll
        for (int i = 0; i < 10; i++) wv[i] = ldg_stream(wp + i * 4096);
#pragma unroll
        for (int i = 0; i < 5; i++) xw[i] = ldg32(P.x + m0 + 2 * i);
    }
    unsigned t0 = 0;
    if (tid >= 256) t0 = gtimer();
    if (tid == 256) {
#pragma unroll
        for (int i = 0; i < B_CKV; i++) asm volatile("mbarrier.init.shared::cta.b64 [%0], 1;" :: "r"(sm + SM_BAR + 8 * i) : "memory");
#pragma unroll
        for (int i = 0; i < B_CKV; i++) asm volatile("mbarrier.arrive.expect_tx.shared::cta.b64 _, [%0], 8192;" :: "r"(sm + SM_BAR + 8 * i) : "memory");
        asm volatile("fence.mbarrier_init.release.cluster;" ::: "memory");
    }
    const int pu = cl < 36 ? cl - 4 : cl - 36, pn = cl < 36 ? 8 : 7;
    const int pv = pu >= 2 * pn ? pu - 2 * pn : pu;
    const int lc = cl < 4 ? cl : cl - pv + (pv >= pn ? 2 * (pv - pn) + 1 : 2 * pv);
    const int b = 2 * lc + r;
    const int h = b >> 2;
    const int pp = lc & 1;
    const int warp = tid >> 5, lane = tid & 31;
    const bool ffn = h < 27;
    Scratch* const S = P.s;

    if (warp < 8) {
        const int g = lane >> 2, t = lane & 3, l7 = lane & 7;
        const int kq = warp >> 1, nh = warp & 1;
        const uint32_t smp = mapa(sm, r ^ 1);
        const int row1 = 2 * l7 + ((lane >> 3) & 1);
        uint32_t a_wuk = sm + SM_WUK + (32 * warp + row1) * 128 + (((lane >> 4) ^ (row1 & 7)) << 4);
        unsigned* p_e2w = reinterpret_cast<unsigned*>(S->e2) + ((cl & 1) * 32 + (cl >> 1)) * 256 + 128 * r + 16 * warp + 8 * (t & 1) + g;
        const uint4* p_e2r = S->e2 + (16 * pp + (tid >> 4)) * 64 + 32 * r + (tid & 15);
        uint32_t a_qsw = sm + SM_QS + (tid >> 4) * 512 + (((tid & 15) ^ ((tid >> 4) & 7)) << 4);
        uint32_t a_qsr = sm + SM_QS + (lane & 15) * 512 + (((lane >> 4) ^ l7) << 4);
        uint32_t a_s = sm + SM_CKV + (16 * warp + l7) * 128 + (((lane >> 3) ^ l7) << 4);
        uint32_t o_spw = warp * 1024 + ((lane ^ (nh << 2)) << 4);
        uint32_t a_ct = sm + SM_CKV + kq * 16384 + lane * 128 + (((4 * nh) ^ l7) << 4);
        uint32_t a_sr = sm + g * 1024 + ((warp ^ (g & 1)) << 6) + t * 16;
        uint2* p_stw = S->st + ((16 * pp + 8 * r + warp) * 32 + h) * STS_ + lane;
        uint4* p_e3w = S->e3 + ((((16 * pp + g) * 2 + r) * 8 + warp) * 32 + h) * 4 + t;
        const uint4* p_e3r = S->e3 + ((h * 2 + r) * 8 + warp) * 128 + lane;
        const int krow = l7 + 8 * (lane >> 4), csel = (lane >> 3) & 1;
        uint32_t a_w1 = sm + SM_W1 + (80 * kq + krow) * 64 + (((2 * nh + csel) ^ (l7 >> 1)) << 4);
        uint32_t a_wuv = sm + SM_WUV + (32 * warp + krow) * 128 + ((csel ^ l7) << 4);
        uint32_t a_fin[5];
#pragma unroll
        for (int i = 0; i < 5; i++) {
            const int N = 10 * (warp & 3) + 2 * i + csel;
            a_fin[i] = sm + (warp >> 2) * 10240 + (N >> 3) * 2048 + krow * 128 + (((N & 7) ^ l7) << 4);
            PIN(a_fin[i]);
        }
        uint32_t b_xc = ((t >> 1) == r ? mapa(sm, r) : smp), b_xh = (nh == r ? mapa(sm, r) : smp);
        uint32_t a_xc = b_xc + SM_XC + (8 * r + warp) * 128 + ((t & 1) * 8 + g) * 8;
        uint32_t a_xh = b_xh + SM_XH + ((t & 1) * 8 + g) * 32 + (4 * r + kq) * 4;
        unsigned* p_e4w = reinterpret_cast<unsigned*>(S->e4) + ((10 * warp + t) * NCTA + b) * 8 + g;
        PIN(a_wuk); PINL(p_e2w); PINL(p_e2r); PIN(a_s); PIN(a_qsw); PIN(a_qsr); PIN(o_spw); PIN(a_ct); PIN(a_sr);
        PINL(p_stw); PINL(p_e3w); PINL(p_e3r); PIN(a_w1); PIN(a_wuv); PIN(a_xc); PIN(a_xh); PINL(p_e4w);

        {
            float acc[8];
#pragma unroll
            for (int e = 0; e < 8; e++) acc[e] = 0.f;
#pragma unroll
            for (int i = 0; i < 10; i++) fma8(acc, (i & 1) ? bf_hi(xw[i >> 1]) : bf_lo(xw[i >> 1]), wv[i]);
            const bool b4 = lane & 16, b3 = lane & 8;
            float k4[4], k2[2];
#pragma unroll
            for (int e = 0; e < 4; e++) k4[e] = (b4 ? acc[4 + e] : acc[e]) + shfl_x(b4 ? acc[e] : acc[4 + e], 16);
#pragma unroll
            for (int e = 0; e < 2; e++) k2[e] = (b3 ? k4[2 + e] : k4[e]) + shfl_x(b3 ? k4[e] : k4[2 + e], 8);
            STAMP(0);
            asm volatile("barrier.cluster.wait.aligned;" ::: "memory");
            const uint32_t o = SM_XQ + (8 * r + warp) * 256 + (4 * l7 + (lane >> 3)) * 8;
            const uint32_t smo = mapa(sm, r);
            st_async2(smp + o, __float_as_uint(k2[0]), __float_as_uint(k2[1]), smp + SM_BAR + 8 * B_XQ);
            st_async2(smo + o, __float_as_uint(k2[0]), __float_as_uint(k2[1]), smo + SM_BAR + 8 * B_XQ);
        }
        bar_sync(1, 288);
        const unsigned tag = lds32(sm + SM_G + 4);
        t0 = lds32(sm + SM_G + 12);
        {
            mbar_wait(sm + SM_BAR + 8 * B_XQ);
            float2 qv[16];
#pragma unroll
            for (int i = 0; i < 16; i++) qv[i] = lds64f(sm + SM_XQ + i * 256 + lane * 8);
#pragma unroll
            for (int i = 0; i < 8; i++) { qv[i].x += qv[i + 8].x; qv[i].y += qv[i + 8].y; }
#pragma unroll
            for (int i = 0; i < 4; i++) { qv[i].x += qv[i + 4].x; qv[i].y += qv[i + 4].y; }
            qv[0].x = (qv[0].x + qv[2].x) + (qv[1].x + qv[3].x);
            qv[0].y = (qv[0].y + qv[2].y) + (qv[1].y + qv[3].y);
            const uint32_t qw = pack_bf16(qv[0].x, qv[0].y);
            uint32_t qb[8];
#pragma unroll
            for (int i = 0; i < 8; i++) qb[i] = __shfl_sync(0xffffffffu, qw, 4 * i + t);
            STAMP(1);
            mbar_wait(sm + SM_BAR + 8 * (B_WUK + kq));
            STAMP_T(224, 20);
            uint32_t a[8][4];
#pragma unroll
            for (int s = 0; s < 8; s++) ldsm4((a_wuk ^ ((s & 3) << 5)) + (s >> 2) * 2048, a[s]);
            float c[4][4];
#pragma unroll
            for (int i = 0; i < 4; i++) {
                c[i][0] = c[i][1] = c[i][2] = c[i][3] = 0.f;
                mma4(c[i], a[2 * i], qb[4 * (i & 1)], qb[4 * (i & 1) + 1]);
            }
#pragma unroll
            for (int i = 0; i < 4; i++) mma4(c[i], a[2 * i + 1], qb[4 * (i & 1) + 2], qb[4 * (i & 1) + 3]);
            const float sc = 0.08838834764831845f * 1.4426950408889634f;
            const float lo = ((t & 1) ? c[2][0] + c[3][0] : c[0][0] + c[1][0]) * sc;
            const float hi = ((t & 1) ? c[2][2] + c[3][2] : c[0][2] + c[1][2]) * sc;
            const uint32_t lob = (lo != lo) ? 0x7FFEu : (((__float_as_uint(lo) + 0x10000u) >> 16) & 0xFFFEu);
            if (t < 2) st_pub1(p_e2w, (pack_bf16(0.f, hi) & 0xFFFF0000u) | lob | tag);
        }
        STAMP_T(224, 2);
        {
            bar_sync(3, 256);
            float s[4][4];
#pragma unroll
            for (int i = 0; i < 4; i++) s[i][0] = s[i][1] = s[i][2] = s[i][3] = 0.f;
            uint32_t ct[4][4][4];
            uint32_t bf[2][4][4];
            uint4 v[4];
#define LOAD_BF(q) _Pragma("unroll") for (int i = 0; i < 4; i++) ldsm4((a_s ^ ((i >> 1) << 6)) + (q) * 16384 + (i & 1) * 1024, bf[(q) & 1][i])
#define LOAD_CT()  _Pragma("unroll") for (int i = 0; i < 16; i++) ldsm4t((a_ct ^ ((i >> 2) << 4)) + (i & 3) * 4096, ct[i >> 2][i & 3])
#define STAGE_Q(st2) do { \
                int it = 0; \
                while ((chk4(chk4(0u, v[2 * (st2)], tag), v[2 * (st2) + 1], tag) & 1u) && ++it < SPIN_MAX) { \
                    v[2 * (st2)] = ld_home4(p_e2r + (st2) * 16); \
                    v[2 * (st2) + 1] = ld_home4(p_e2r + (st2) * 16 + 2048); \
                } \
                PROF_ROUNDS(st2 ? 28 : 18, it); \
                const uint4 &x = v[2 * (st2)], &y = v[2 * (st2) + 1]; \
                sts128u(a_qsw + (st2) * 256, add_bf16x2(x.x, y.x), add_bf16x2(x.y, y.y), add_bf16x2(x.z, y.z), add_bf16x2(x.w, y.w)); \
            } while (0)
#define LOAD_QA(q) _Pragma("unroll") for (int i = 0; i < 4; i++) ldsm4((a_qsr ^ (i << 5)) + (q) * 128, qa[(q) & 1][i])
#define S_BLOCK(q) do { \
                const uint32_t (&A)[4][4] = qa[(q) & 1]; const uint32_t (&B)[4][4] = bf[(q) & 1]; \
                mma4(s[0], A[0], B[0][0], B[0][1]); mma4(s[1], A[0], B[1][0], B[1][1]); \
                mma4(s[2], A[1], B[0][2], B[0][3]); mma4(s[3], A[1], B[1][2], B[1][3]); \
                mma4(s[0], A[2], B[2][0], B[2][1]); mma4(s[1], A[2], B[3][0], B[3][1]); \
                mma4(s[2], A[3], B[2][2], B[2][3]); mma4(s[3], A[3], B[3][2], B[3][3]); \
            } while (0)
            uint32_t qa[2][4][4];
            while (gtimer() - t0 < TA_NS) {}
            STAMP(19);
            v[0] = ld_poll4(p_e2r);
            v[1] = ld_poll4(p_e2r + 2048);
            mbar_wait(sm + SM_BAR + 8 * (B_CKV + 0));
            LOAD_BF(0);
            STAGE_Q(0);
            STAMP(26);
            while (gtimer() - t0 < TB_NS) {}
            v[2] = ld_poll4(p_e2r + 16);
            v[3] = ld_poll4(p_e2r + 16 + 2048);
            mbar_wait(sm + SM_BAR + 8 * (B_CKV + 1));
            LOAD_BF(1);
            bar_sync(3, 256);
            LOAD_QA(0);
            LOAD_QA(1);
            S_BLOCK(0);
            S_BLOCK(1);
            if (kq < CTE) { LOAD_CT(); }
            mbar_wait(sm + SM_BAR + 8 * (B_CKV + 2));
            LOAD_BF(2);
            STAMP(11);
            STAGE_Q(1);
            STAMP(3);
            bar_sync(3, 256);
            LOAD_QA(2);
            LOAD_QA(3);
            mbar_wait(sm + SM_BAR + 8 * (B_CKV + 3));
            STAMP(4);
            LOAD_BF(3);
            S_BLOCK(2);
            S_BLOCK(3);
            {
                const float u0 = s[0][0] + s[2][0], u1 = s[0][1] + s[2][1], u2 = s[1][0] + s[3][0], u3 = s[1][1] + s[3][1];
                const float v0 = s[0][2] + s[2][2], v1 = s[0][3] + s[2][3], v2 = s[1][2] + s[3][2], v3 = s[1][3] + s[3][3];
                st_async4(smp + SM_SPR + o_spw, u0, u1, u2, u3, smp + SM_BAR + 8 * B_SP);
                st_async4(smp + SM_SPR + 512 + o_spw, v0, v1, v2, v3, smp + SM_BAR + 8 * B_SP);
                sts128(sm + SM_SPL + o_spw, u0, u1, u2, u3);
                sts128(sm + SM_SPL + 512 + o_spw, v0, v1, v2, v3);
            }
            if (kq >= CTE) { LOAD_CT(); }
            bar_sync(3, 256);
            STAMP(5);
            {
                const uint4 ul = lds128(a_sr + SM_SPL), vl = lds128(a_sr + SM_SPL + 512);
                mbar_wait(sm + SM_BAR + 8 * B_SP);
                STAMP(6);
                const uint4 ur = lds128(a_sr + SM_SPR), vr = lds128(a_sr + SM_SPR + 512);
                const float u0 = __uint_as_float(ul.x) + __uint_as_float(ur.x), u1 = __uint_as_float(ul.y) + __uint_as_float(ur.y);
                const float u2 = __uint_as_float(ul.z) + __uint_as_float(ur.z), u3 = __uint_as_float(ul.w) + __uint_as_float(ur.w);
                const float v0 = __uint_as_float(vl.x) + __uint_as_float(vr.x), v1 = __uint_as_float(vl.y) + __uint_as_float(vr.y);
                const float v2 = __uint_as_float(vl.z) + __uint_as_float(vr.z), v3 = __uint_as_float(vl.w) + __uint_as_float(vr.w);
                const float mu = warp_max(fmaxf(fmaxf(u0, u1), fmaxf(u2, u3)));
                const float mv = warp_max(fmaxf(fmaxf(v0, v1), fmaxf(v2, v3)));
                const uint32_t a0 = pack_bf16(ex2(u0 - mu), ex2(u1 - mu)), a2 = pack_bf16(ex2(u2 - mu), ex2(u3 - mu));
                const uint32_t a1 = pack_bf16(ex2(v0 - mv), ex2(v1 - mv)), a3 = pack_bf16(ex2(v2 - mv), ex2(v3 - mv));
                sts128u(sm + SM_P + g * 512 + warp * 64 + t * 16, a0, a1, a2, a3);
                bar_sync(2, 288);
                STAMP(7);
                uint4 pa[8];
#pragma unroll
                for (int q = 0; q < 8; q++) pa[q] = lds128(sm + SM_P + q * 512 + lane * 16);
                float o[2][4][4];
#pragma unroll
                for (int n = 0; n < 4; n++)
#pragma unroll
                    for (int e = 0; e < 4; e++) o[0][n][e] = o[1][n][e] = 0.f;
#pragma unroll
                for (int i = 0; i < 4; i++) {
#pragma unroll
                    for (int n = 0; n < 4; n++) mma(o[0][n], pa[2 * i].x, pa[2 * i].y, pa[2 * i].z, pa[2 * i].w, ct[n][i][0], ct[n][i][1]);
#pragma unroll
                    for (int n = 0; n < 4; n++) mma(o[1][n], pa[2 * i + 1].x, pa[2 * i + 1].y, pa[2 * i + 1].z, pa[2 * i + 1].w, ct[n][i][2], ct[n][i][3]);
                }
                const uint32_t q0 = r ? a1 : a0, q1 = r ? a3 : a2;
                float l = (bf_lo(q0) + bf_hi(q0)) + (bf_lo(q1) + bf_hi(q1));
#pragma unroll
                for (int d = 1; d < 32; d <<= 1) l += shfl_x(l, d);
                if (lane < (STS_ < 4 ? STS_ : 4)) st_pub64(p_stw, tagf(l, tag), __float_as_uint(r ? mv : mu));
                uint32_t w0[4], w1[4];
#pragma unroll
                for (int n = 0; n < 4; n++) {
                    w0[n] = pack_bf16(o[0][n][0] + o[1][n][0], o[0][n][1] + o[1][n][1]);
                    w1[n] = pack_bf16(o[0][n][2] + o[1][n][2], o[0][n][3] + o[1][n][3]);
                }
                st_pub2x64(p_e3w, tagw(w0[0], tag), w0[1], tagw(w0[2], tag), w0[3]);
                st_pub2x64(p_e3w + 8 * 2 * 8 * 32 * 4, tagw(w1[0], tag), w1[1], tagw(w1[2], tag), w1[3]);
            }
        }
        STAMP(8);
        if (ffn) {
            const uint32_t xa = sm + SM_XS + 160 * kq + 4 * t;
            uint32_t xb[5][2];
#pragma unroll
            for (int s = 0; s < 5; s++) { xb[s][0] = lds32(xa + s * 32); xb[s][1] = lds32(xa + s * 32 + 16); }
            mbar_wait(sm + SM_BAR + 8 * (B_W1 + (warp >> 2)));
            uint32_t a[5][4];
#pragma unroll
            for (int s = 0; s < 5; s++) ldsm4t(a_w1 + s * 1024, a[s]);
            float c0[4] = {0.f, 0.f, 0.f, 0.f}, c1[4] = {0.f, 0.f, 0.f, 0.f};
#pragma unroll
            for (int s = 0; s < 5; s++) mma4((s & 1) ? c1 : c0, a[s], xb[s][0], xb[s][1]);
            if (t < 2) st_async1(a_xh, t ? c0[2] + c1[2] : c0[0] + c1[0], b_xh + SM_BAR + 8 * B_XH);
        }
        STAMP(9);
        float invl;
        {
            uint32_t a[8][4];
            mbar_wait(sm + SM_BAR + 8 * (B_WUV + kq));
#pragma unroll
            for (int i = 0; i < 8; i++) ldsm4t((a_wuv ^ ((i >> 1) << 5)) + (i & 1) * 2048, a[i]);
            uint4 v[4];
            uint32_t fw[4];
            int it = 0;
            bar_sync(4, 288);
#pragma unroll
            for (int i = 0; i < 4; i++) v[i] = ld_poll2x64(p_e3r + i * 32);
            STAMP(24);
#pragma unroll
            for (int i = 0; i < 4; i++) fw[i] = lds32(sm + SM_F + (8 * i + g) * 4);
            invl = __uint_as_float(lds32(sm + SM_G + 8));
            while (true) {
                unsigned bad = 0u;
#pragma unroll
                for (int i = 0; i < 4; i++) bad = chk(chk(bad, v[i].x, tag), v[i].z, tag);
                if (!(bad & 1u) || ++it >= SPIN_MAX) break;
#pragma unroll
                for (int i = 0; i < 4; i++) v[i] = ld_home4(p_e3r + i * 32);
            }
            PROF_ROUNDS(25, it);
            __syncwarp();
            STAMP(10);
            uint32_t bx = mul_bf16x2(fw[0], v[0].x & ~1u), by = mul_bf16x2(fw[0], v[0].y), bz = mul_bf16x2(fw[0], v[0].z & ~1u), bw = mul_bf16x2(fw[0], v[0].w);
#pragma unroll
            for (int i = 1; i < 4; i++) {
                bx = fma_bf16x2(fw[i], v[i].x & ~1u, bx); by = fma_bf16x2(fw[i], v[i].y, by);
                bz = fma_bf16x2(fw[i], v[i].z & ~1u, bz); bw = fma_bf16x2(fw[i], v[i].w, bw);
            }
            float c[4][4];
#pragma unroll
            for (int i = 0; i < 4; i++) {
                c[i][0] = c[i][1] = c[i][2] = c[i][3] = 0.f;
                mma4(c[i], a[2 * i], bx, by);
            }
#pragma unroll
            for (int i = 0; i < 4; i++) mma4(c[i], a[2 * i + 1], bz, bw);
            float e[8], k4[4];
#pragma unroll
            for (int i = 0; i < 4; i++) { e[2 * i] = c[i][0] + c[i][1]; e[2 * i + 1] = c[i][2] + c[i][3]; }
            const bool t1 = t & 2, t0 = t & 1;
#pragma unroll
            for (int i = 0; i < 4; i++) k4[i] = (t1 ? e[4 + i] : e[i]) + shfl_x(t1 ? e[i] : e[4 + i], 2);
            const float k0 = (t0 ? k4[2] : k4[0]) + shfl_x(t0 ? k4[0] : k4[2], 1);
            const float k1 = (t0 ? k4[3] : k4[1]) + shfl_x(t0 ? k4[1] : k4[3], 1);
            st_async2(a_xc, __float_as_uint(k0), __float_as_uint(k1), b_xc + SM_BAR + 8 * B_XC);
        }
        STAMP(12);
        {
            float c[5][4];
#pragma unroll
            for (int i = 0; i < 5; i++) c[i][0] = c[i][1] = c[i][2] = c[i][3] = 0.f;
            const int half = warp >> 2;
            const float gt = __uint_as_float(lds32(sm + SM_G));
            if (ffn) {
                mbar_wait(sm + SM_BAR + 8 * B_XH);
                const uint4 u = lds128(sm + SM_XH + (lane & 15) * 32), v = lds128(sm + SM_XH + (lane & 15) * 32 + 16);
                float hv = ((__uint_as_float(u.x) + __uint_as_float(u.y)) + (__uint_as_float(u.z) + __uint_as_float(u.w))) +
                           ((__uint_as_float(v.x) + __uint_as_float(v.y)) + (__uint_as_float(v.z) + __uint_as_float(v.w)));
                hv = bf_lo(pack_bf16(hv, 0.f));
                hv = __fdividef(hv, 1.f + __expf(-hv)) * (1.f - gt);
                const uint32_t w = pack_bf16(hv, shfl_x(hv, 1));
                const uint32_t b0 = __shfl_sync(0xffffffffu, w, 2 * t), b1 = __shfl_sync(0xffffffffu, w, 8 + 2 * t);
                mbar_wait(sm + SM_BAR + 8 * (B_W2 + half));
                uint32_t a[5][4];
#pragma unroll
                for (int i = 0; i < 5; i++) ldsm4t(a_fin[i] + SM_W2, a[i]);
#pragma unroll
                for (int i = 0; i < 5; i++) mma4(c[i], a[i], b0, b1);
            }
            uint32_t wa[2][5][4];
            mbar_wait(sm + SM_BAR + 8 * (B_WO + half));
#pragma unroll
            for (int i = 0; i < 5; i++) ldsm4t(a_fin[i] + SM_WO, wa[0][i]);
            const bool early = mbar_test(sm + SM_BAR + 8 * (B_WO + 2 + half));
            if (early) {
#pragma unroll
                for (int i = 0; i < 5; i++) ldsm4t(a_fin[i] + SM_WO + 20480, wa[1][i]);
            }
            mbar_wait(sm + SM_BAR + 8 * B_XC);
            STAMP(13);
            float xv[16];
#pragma unroll
            for (int i = 0; i < 16; i++) xv[i] = __uint_as_float(lds32(sm + SM_XC + i * 128 + lane * 4));
#pragma unroll
            for (int i = 0; i < 8; i++) xv[i] += xv[i + 8];
            const float cv = (((xv[0] + xv[4]) + (xv[1] + xv[5])) + ((xv[2] + xv[6]) + (xv[3] + xv[7]))) * (gt * invl);
            const uint32_t w = pack_bf16(cv, shfl_x(cv, 2));
            uint32_t bb[4];
#pragma unroll
            for (int q = 0; q < 4; q++) bb[q] = __shfl_sync(0xffffffffu, w, (q >> 1) * 16 + 4 * t + (q & 1));
#pragma unroll
            for (int i = 0; i < 5; i++) mma4(c[i], wa[0][i], bb[0], bb[1]);
            if (!early) {
                mbar_wait(sm + SM_BAR + 8 * (B_WO + 2 + half));
#pragma unroll
                for (int i = 0; i < 5; i++) ldsm4t(a_fin[i] + SM_WO + 20480, wa[1][i]);
            }
#pragma unroll
            for (int i = 0; i < 5; i++) mma4(c[i], wa[1][i], bb[2], bb[3]);
            STAMP_T(224, 14);
            const bool t0 = t & 1, t1 = t & 2;
            const float v0 = t1 ? (t0 ? c[1][2] : c[1][0]) : (t0 ? c[0][2] : c[0][0]);
            const float v1 = t1 ? (t0 ? c[3][2] : c[3][0]) : (t0 ? c[2][2] : c[2][0]);
            const float v2 = t0 ? c[4][2] : c[4][0];
            st_pub1(p_e4w, tagf(v0, tag));
            st_pub1(p_e4w + 4 * NCTA * 8, tagf(v1, tag));
            if (!t1) st_pub1(p_e4w + 8 * NCTA * 8, tagf(v2, tag));
        }
        STAMP_T(224, 15);
        if (b < 80) {
            const uint4* p = S->e4 + b * NCTA * 2 + tid;
            spin_until(clock32() + D4);
            uint4 v;
            int it = 0;
            do { v = ld_poll4(p); } while ((chk4(0u, v, tag) & 1u) && ++it < SPIN_MAX);
            __syncwarp();
            STAMP(16);
            const bool b4 = lane & 16, b3 = lane & 8;
            const float k0 = untagf(b4 ? v.z : v.x) + shfl_x(untagf(b4 ? v.x : v.z), 16);
            const float k1 = untagf(b4 ? v.w : v.y) + shfl_x(untagf(b4 ? v.y : v.w), 16);
            float s = (b3 ? k1 : k0) + shfl_x(b3 ? k0 : k1, 8);
            s += shfl_x(s, 4);
            s += shfl_x(s, 2);
            if (!(lane & 6)) sts32(sm + SM_FIN + ((lane & 1) * 4 + (lane >> 3)) * 32 + warp * 4, __float_as_uint(s));
            bar_sync(3, 256);
            if (tid < 8) {
                const uint4 u = lds128(sm + SM_FIN + tid * 32), w = lds128(sm + SM_FIN + tid * 32 + 16);
                P.out[b * 8 + tid] = __float2bfloat16(((__uint_as_float(u.x) + __uint_as_float(u.y)) + (__uint_as_float(u.z) + __uint_as_float(u.w))) +
                                                      ((__uint_as_float(w.x) + __uint_as_float(w.y)) + (__uint_as_float(w.z) + __uint_as_float(w.w))));
                if (b == 0 && tid == 0) st_pub1(&S->epoch, tag);
            }
            STAMP(17);
        }
    } else if (warp == 8) {
        const uint32_t bar = sm + SM_BAR + 8 * lane;
        __syncwarp();
        asm volatile("barrier.cluster.arrive.relaxed.aligned;" ::: "memory");
        if (lane < 6) asm volatile("prefetch.tensormap [%0];" :: "l"(&P.m[lane]) : "memory");
        float warm[4] = {0.f, 0.f, 0.f, 0.f};
        {
            int map, c0 = 0, c1, c2;
            uint32_t dst, bytes, due;
            const int k = lane;
            constexpr int DF = DT_NS * 135 / 128;
            if (k < B_CKV)      { map = 0; c1 = 256 * r + 64 * k;            c2 = cl;                 dst = SM_WUK + k * 8192;            bytes = 8192;  due = k * DT_NS; }
            else if (k < B_W1)  { map = 1; c1 = 128 * h;                     c2 = 4 * r + k - B_CKV;  dst = SM_CKV + (k - B_CKV) * 16384; bytes = 16384; due = k * DT_NS; }
            else if (k < B_WUV) { map = 2; c1 = 320 * r + 160 * (k - B_W1);  c2 = h; c0 = 32 * pp;    dst = SM_W1 + (k - B_W1) * 10240;   bytes = ffn ? 10240 : 0; due = 8 * DT_NS + (k - B_W1) * DF; }
            else if (k < B_W2)  { map = 3; c1 = 256 * r + 64 * (k - B_WUV);  c2 = 2 * h + pp;         dst = SM_WUV + (k - B_WUV) * 8192;  bytes = 8192;  due = (k - 2) * DT_NS + 2 * DF; }
            else if (k < B_WO)  { map = 4; c1 = 16 * b;                      c2 = 5 * (k - B_W2);     dst = SM_W2 + (k - B_W2) * 10240;   bytes = ffn ? 10240 : 0; due = 12 * DT_NS + 2 * DF + (k - B_W2) * (DT2_NS * 135 / 128); }
            else                { map = 5; c1 = 32 * b + 16 * ((k - B_WO) >> 1); c2 = 5 * (k & 1);    dst = SM_WO + (k - B_WO) * 10240;   bytes = k < B_SP ? 10240 : 0;
                                  due = 12 * DT_NS + 2 * DF + 2 * (DT2_NS * 135 / 128) + (k - B_WO) * (DT2_NS * 5 / 4); }
            due += T0_NS;
            {
                constexpr int gap[20] = SCHED;
                due = 0;
#pragma unroll
                for (int i = 0; i < 20; i++) due += (i <= k) ? gap[i] : 0;
                due += ((b * 37) & 127) * (k < 4 ? STAG_A : STAG_B) / 128;
            }
            bool pending = bytes != 0;
            STAMP_T(256, 21);
            bool first = true;
            while (__any_sync(0xffffffffu, pending)) {
                if (first && !__any_sync(0xffffffffu, pending && k < B_CKV)) { bar_sync(5, 64); first = false; }
                const unsigned now = gtimer() - t0;
                if (pending && now >= due && (k < B_CKV || !first)) {
                    asm volatile("cp.async.bulk.tensor.3d.shared::cluster.global.mbarrier::complete_tx::bytes [%0], [%1, {%3,%4,%5}], [%2];"
                                 :: "r"(sm + dst), "l"(&P.m[map]), "r"(bar), "r"(c0), "r"(c1), "r"(c2) : "memory");
                    pending = false;
                }
            }
        }
        if (lane >= B_W2 && lane < B_SP && (ffn || lane >= B_WO)) mbar_wait(bar);
        STAMP_T(256, 22);
    } else {
        const unsigned old = ld_poll1(&S->epoch) & 1u;
        uint32_t xv[10], gw[10];
#pragma unroll
        for (int i = 0; i < 10; i++) {
            xv[i] = ldg32(P.x + (i * 32 + lane) * 2);
            gw[i] = ldg32(P.gate + (i * 32 + lane) * 2);
        }
        if (lane == 0) {
#pragma unroll
            for (int i = B_CKV; i < NBAR; i++) asm volatile("mbarrier.init.shared::cta.b64 [%0], 1;" :: "r"(sm + SM_BAR + 8 * i) : "memory");
#pragma unroll
            for (int i = B_CKV; i < NBAR; i++) {
                const uint32_t tx = i < B_W1 ? 16384 : i < B_WUV ? 10240 : i < B_W2 ? 8192 : i < B_SP ? 10240 :
                                    i == B_SP ? 8192 : i == B_XC ? 2048 : i == B_XH ? 512 : 4096;
                asm volatile("mbarrier.arrive.expect_tx.shared::cta.b64 _, [%0], %1;" :: "r"(sm + SM_BAR + 8 * i), "r"(tx) : "memory");
            }
            asm volatile("fence.mbarrier_init.release.cluster;" ::: "memory");
        }
        __syncwarp();
        asm volatile("barrier.cluster.arrive.relaxed.aligned;" ::: "memory");
        bar_arrive(5, 64);
        st_pub4(S->e2 + ((cl & 1) * 32 + (cl >> 1)) * 64 + 32 * r + lane, old, old, old, old);
        if ((lane & 3) < STS_) st_pub64(S->st + ((16 * pp + 8 * r + (lane >> 2)) * 32 + h) * STS_ + (lane & 3), old, 0u);
        if (lane == 0) { sts32(sm + SM_G + 4, old ^ 1u); sts32(sm + SM_G + 12, t0); }
#pragma unroll
        for (int i = 0; i < 5; i++) st_pub4(&S->e4[((i * 16 + (lane >> 1)) * NCTA + b) * 2 + (lane & 1)], old, old, old, old);
        float z = 0.f;
#pragma unroll
        for (int i = 0; i < 10; i++) {
            if ((i >= 5) == (r != 0)) sts32(sm + SM_XS + ((i % 5) * 32 + lane) * 4, xv[i]);
            z = fmaf(bf_lo(xv[i]), bf_lo(gw[i]), z);
            z = fmaf(bf_hi(xv[i]), bf_hi(gw[i]), z);
        }
#pragma unroll
        for (int d = 1; d < 32; d <<= 1) z += shfl_x(z, d);
        if (lane == 0) sts32(sm + SM_G, __float_as_uint(__fdividef(1.f, 1.f + __expf(-z))));
        bar_arrive(1, 288);
        {
            const uint2* p_str = S->st + (h * 32 + lane) * STS_;
            bar_sync(2, 288);
            spin_until(clock32() + D3);
            uint2 st;
            int it = 0;
            while (true) {
                const unsigned tn = clock32() + D6;
                asm volatile("{.reg .b64 a; atom.relaxed.gpu.global.or.b64 a, [%2], 0; mov.b64 {%0,%1}, a;}" : "=r"(st.x), "=r"(st.y) : "l"(p_str) : "memory");
                if (__all_sync(0xffffffffu, (st.x ^ old) & 1u) || ++it >= SPIN_MAX) break;
                spin_until(tn);
            }
            const unsigned tg = clock32() + D5;
            PROF_ROUNDS(27, it);
            const float M = warp_max(__uint_as_float(st.y));
            const float ff = ex2(__uint_as_float(st.y) - M);
            const uint32_t f2 = pack_bf16(ff, ff);
            sts32(sm + SM_F + lane * 4, f2);
            float L = bf_lo(f2) * untagf(st.x);
#pragma unroll
            for (int d = 1; d < 32; d <<= 1) L += shfl_x(L, d);
            if (lane == 0) sts32(sm + SM_G + 8, __float_as_uint(__fdividef(1.f, L)));
            spin_until(tg);
            bar_arrive(4, 288);
        }
    }
}

#define W1PROMO CU_TENSOR_MAP_L2_PROMOTION_NONE
typedef CUresult (*EncodeFn)(CUtensorMap*, CUtensorMapDataType, cuuint32_t, void*, const cuuint64_t*, const cuuint64_t*,
                             const cuuint32_t*, const cuuint32_t*, CUtensorMapInterleave, CUtensorMapSwizzle,
                             CUtensorMapL2promotion, CUtensorMapFloatOOBfill);

void make_map(EncodeFn enc, CUtensorMap* m, const void* base, int rows, int cols, int box_cols, int box_rows, int box_blks) {
    cuuint64_t gd[3] = {64, (cuuint64_t)rows, (cuuint64_t)(cols / 64)};
    cuuint64_t gs[2] = {(cuuint64_t)cols * 2, 128};
    cuuint32_t bd[3] = {(cuuint32_t)box_cols, (cuuint32_t)box_rows, (cuuint32_t)box_blks};
    cuuint32_t es[3] = {1, 1, 1};
    enc(m, CU_TENSOR_MAP_DATA_TYPE_BFLOAT16, 3, const_cast<void*>(base), gd, gs, bd, es, CU_TENSOR_MAP_INTERLEAVE_NONE,
        box_cols == 64 ? CU_TENSOR_MAP_SWIZZLE_128B : CU_TENSOR_MAP_SWIZZLE_64B,
        W1PROMO, CU_TENSOR_MAP_FLOAT_OOB_FILL_NONE);
}

}

extern "C" void kernel_launch(void* const* d_in, const int* in_sizes, int n_in, void* d_out, int out_size) {
    (void)in_sizes; (void)n_in; (void)out_size;
    constexpr int smem_bytes = SMEM_BYTES;
    static EncodeFn enc = nullptr;
    static Scratch* scratch = nullptr;
    if (!enc) {
        void* fn = nullptr;
        cudaDriverEntryPointQueryResult st;
        cudaGetDriverEntryPoint("cuTensorMapEncodeTiled", &fn, cudaEnableDefault, &st);
        enc = (EncodeFn)fn;
        cudaFuncSetAttribute(fused_kernel, cudaFuncAttributeMaxDynamicSharedMemorySize, smem_bytes);
        cudaGetSymbolAddress((void**)&scratch, g_s);
    }
    Params p;
    make_map(enc, &p.m[0], d_in[3], 512, 4096, 64, 64, 1);
    make_map(enc, &p.m[1], d_in[1], 4096, 512, 64, 128, 1);
    make_map(enc, &p.m[2], d_in[7], 640, 1728, 32, 160, 1);
    make_map(enc, &p.m[3], d_in[4], 512, 4096, 64, 64, 1);
    make_map(enc, &p.m[4], d_in[8], 1728, 640, 64, 16, 5);
    make_map(enc, &p.m[5], d_in[5], 4096, 640, 64, 16, 5);
    make_map(enc, &p.m[6], d_in[2], 640, 4096, 64, 160, 1);
    p.x = (const __nv_bfloat16*)d_in[0];
    p.wq = (const __nv_bfloat16*)d_in[2];
    p.gate = (const __nv_bfloat16*)d_in[9];
    p.out = (__nv_bfloat16*)d_out;
    p.s = scratch;
    fused_kernel<<<NCTA, NTHREADS, smem_bytes>>>(p);
}
```

```cpp
#include <cuda_runtime.h>
#include <cuda.h>
#include <cuda_bf16.h>
#include <stdint.h>

namespace {

constexpr int NCTA = 128;
constexpr int NTHREADS = 320;
constexpr int SPIN_MAX = 1 << 18;

constexpr int SM_WUK = 0;
constexpr int SM_CKV = SM_WUK + 32768;
constexpr int SM_WUV = SM_CKV + 65536;
constexpr int SM_WO  = SM_WUV + 32768;
constexpr int SM_W1  = SM_WO + 40960;
constexpr int SM_W2  = SM_CKV;
constexpr int SM_SPR = SM_W1 + 20480;
constexpr int SM_QS  = SM_WUK;
constexpr int SM_SPL = SM_WUK + 8192;
constexpr int SM_P   = SM_WUK + 16384;
constexpr int SM_FIN = SM_WUK + 20480;
constexpr int SM_XC  = SM_WUK + 24576;
constexpr int SM_XH  = SM_XC + 2048;
constexpr int SM_XQ  = SM_SPR + 8192;
constexpr int SM_XS  = SM_XQ + 4096;
constexpr int SM_G   = SM_XS + 640;
constexpr int SM_F   = SM_G + 32;
constexpr int SM_BAR = SM_F + 128;
constexpr int SMEM_BYTES = SM_BAR + 32 * 8;
static_assert(SMEM_BYTES <= 232448, "smem");

constexpr int B_WUK = 0, B_CKV = 4, B_W1 = 8, B_WUV = 10, B_WO = 14, B_W2 = 18, B_SP = 19, B_XC = 20, B_XH = 21, B_XQ = 22, B_FB = 23, B_DEAD = 24, NBAR = 25;
constexpr int NCHUNK = 22;

struct Scratch {
    uint4    e3[32 * 2 * 8 * 32 * 4];
    uint4    e4[80 * NCTA * 2];
    uint4    e2[2 * 32 * 64];
    uint2    st[32 * 32 * 4];
    uint4    eh[432];
    unsigned epoch;
};
__device__ __align__(1024) Scratch g_s;

struct Params {
    const __nv_bfloat16* wq;
    const __nv_bfloat16* x;
    Scratch* s;
    const __nv_bfloat16* gate;
    __nv_bfloat16* out;
    int due[32], stag[32];
    int d3, d4, d5, d6, ta, tb;
    alignas(64) CUtensorMap m[6];
};

#define STAMP(i)
#define COUNT(i, it)

__device__ __forceinline__ unsigned clock32() { unsigned c; asm volatile("mov.u32 %0, %%clock;" : "=r"(c) :: "memory"); return c; }
__device__ __forceinline__ unsigned gtimer() { unsigned c; asm volatile("mov.u32 %0, %%globaltimer_lo;" : "=r"(c) :: "memory"); return c; }

__device__ __forceinline__ uint4 ldg_stream(const void* p) {
    uint4 v;
    asm volatile("ld.global.nc.L1::no_allocate.v4.u32 {%0,%1,%2,%3}, [%4];"
                 : "=r"(v.x), "=r"(v.y), "=r"(v.z), "=r"(v.w) : "l"(p));
    return v;
}
__device__ __forceinline__ uint4 ld_poll4(const void* p) {
    uint4 v;
    asm volatile("ld.relaxed.gpu.global.v4.u32 {%0,%1,%2,%3}, [%4];"
                 : "=r"(v.x), "=r"(v.y), "=r"(v.z), "=r"(v.w) : "l"(p) : "memory");
    return v;
}
__device__ __forceinline__ uint4 ld_poll2x64(const void* p) {
    uint4 v;
    asm volatile("{.reg .b64 a, b; ld.relaxed.gpu.global.v2.b64 {a, b}, [%4]; mov.b64 {%0,%1}, a; mov.b64 {%2,%3}, b;}"
                 : "=r"(v.x), "=r"(v.y), "=r"(v.z), "=r"(v.w) : "l"(p) : "memory");
    return v;
}
__device__ __forceinline__ uint2 ld_poll64(const void* p) {
    uint2 v;
    asm volatile("{.reg .b64 a; ld.relaxed.gpu.global.b64 a, [%2]; mov.b64 {%0,%1}, a;}" : "=r"(v.x), "=r"(v.y) : "l"(p) : "memory");
    return v;
}
__device__ __forceinline__ unsigned ld_poll1(const void* p) {
    unsigned v;
    asm volatile("ld.relaxed.gpu.global.u32 %0, [%1];" : "=r"(v) : "l"(p) : "memory");
    return v;
}
__device__ __forceinline__ void st_pub2x64(void* p, unsigned a, unsigned b, unsigned c, unsigned d) {
    asm volatile("{.reg .b64 x, y; mov.b64 x, {%1,%2}; mov.b64 y, {%3,%4}; st.relaxed.gpu.global.v2.b64 [%0], {x, y};}"
                 :: "l"(p), "r"(a), "r"(b), "r"(c), "r"(d) : "memory");
}
__device__ __forceinline__ void st_pub64(void* p, unsigned a, unsigned b) {
    asm volatile("{.reg .b64 x; mov.b64 x, {%1,%2}; st.relaxed.gpu.global.b64 [%0], x;}" :: "l"(p), "r"(a), "r"(b) : "memory");
}
__device__ __forceinline__ void st_pub1(void* p, unsigned a) {
    asm volatile("st.relaxed.gpu.global.u32 [%0], %1;" :: "l"(p), "r"(a) : "memory");
}
__device__ __forceinline__ unsigned tagw(unsigned w, unsigned tag) { return (w & ~1u) | tag; }
__device__ __forceinline__ unsigned tagf(float v, unsigned tag) { return (__float_as_uint(v) & ~1u) | tag; }
__device__ __forceinline__ float untagf(unsigned w) { return __uint_as_float(w & ~1u); }

__device__ __forceinline__ void mbar_wait(uint32_t bar) {
    uint32_t ok;
    int it = 0;
#pragma unroll 1
    do {
        asm volatile("{.reg .pred p; mbarrier.try_wait.parity.shared::cta.b64 p, [%1], 0; selp.u32 %0,1,0,p;}"
                     : "=r"(ok) : "r"(bar) : "memory");
    } while (!ok && ++it < SPIN_MAX);
}
__device__ __forceinline__ void bar_sync(int id, int n) { asm volatile("bar.sync %0, %1;" :: "r"(id), "r"(n) : "memory"); }
__device__ __forceinline__ void bar_arrive(int id, int n) { asm volatile("bar.arrive %0, %1;" :: "r"(id), "r"(n) : "memory"); }
__device__ __forceinline__ uint32_t mapa(uint32_t a, uint32_t rank) {
    uint32_t r;
    asm("mapa.shared::cluster.u32 %0, %1, %2;" : "=r"(r) : "r"(a), "r"(rank));
    return r;
}
__device__ __forceinline__ void st_async4(uint32_t a, float x, float y, float z, float w, uint32_t bar) {
    asm volatile("st.async.weak.shared::cluster.mbarrier::complete_tx::bytes.v4.f32 [%0], {%1,%2,%3,%4}, [%5];"
                 :: "r"(a), "f"(x), "f"(y), "f"(z), "f"(w), "r"(bar) : "memory");
}
__device__ __forceinline__ void st_async2(uint32_t a, uint32_t x, uint32_t y, uint32_t bar) {
    asm volatile("st.async.weak.shared::cluster.mbarrier::complete_tx::bytes.v2.b32 [%0], {%1,%2}, [%3];"
                 :: "r"(a), "r"(x), "r"(y), "r"(bar) : "memory");
}

__device__ __forceinline__ void ldsm4(uint32_t a, uint32_t (&r)[4]) {
    asm volatile("ldmatrix.sync.aligned.m8n8.x4.shared.b16 {%0,%1,%2,%3}, [%4];"
                 : "=r"(r[0]), "=r"(r[1]), "=r"(r[2]), "=r"(r[3]) : "r"(a) : "memory");
}
__device__ __forceinline__ void ldsm4t(uint32_t a, uint32_t (&r)[4]) {
    asm volatile("ldmatrix.sync.aligned.m8n8.x4.trans.shared.b16 {%0,%1,%2,%3}, [%4];"
                 : "=r"(r[0]), "=r"(r[1]), "=r"(r[2]), "=r"(r[3]) : "r"(a) : "memory");
}
__device__ __forceinline__ void mma(float (&c)[4], uint32_t a0, uint32_t a1, uint32_t a2, uint32_t a3, uint32_t b0, uint32_t b1) {
    asm("mma.sync.aligned.m16n8k16.row.col.f32.bf16.bf16.f32 {%0,%1,%2,%3}, {%4,%5,%6,%7}, {%8,%9}, {%0,%1,%2,%3};"
        : "+f"(c[0]), "+f"(c[1]), "+f"(c[2]), "+f"(c[3])
        : "r"(a0), "r"(a1), "r"(a2), "r"(a3), "r"(b0), "r"(b1));
}
__device__ __forceinline__ uint32_t pack_bf16(float lo, float hi) {
    uint32_t r;
    asm("cvt.rn.bf16x2.f32 %0, %1, %2;" : "=r"(r) : "f"(hi), "f"(lo));
    return r;
}
__device__ __forceinline__ float bf_lo(uint32_t w) { return __uint_as_float(w << 16); }
__device__ __forceinline__ float bf_hi(uint32_t w) { return __uint_as_float(w & 0xFFFF0000u); }
__device__ __forceinline__ float ex2(float x) { float y; asm("ex2.approx.ftz.f32 %0, %1;" : "=f"(y) : "f"(x)); return y; }
__device__ __forceinline__ uint4 lds128(uint32_t a) {
    uint4 v;
    asm volatile("ld.shared.v4.u32 {%0,%1,%2,%3}, [%4];" : "=r"(v.x), "=r"(v.y), "=r"(v.z), "=r"(v.w) : "r"(a) : "memory");
    return v;
}
__device__ __forceinline__ float2 lds64f(uint32_t a) {
    float2 v;
    asm volatile("ld.shared.v2.f32 {%0,%1}, [%2];" : "=f"(v.x), "=f"(v.y) : "r"(a) : "memory");
    return v;
}
__device__ __forceinline__ uint32_t lds32(uint32_t a) {
    uint32_t v;
    asm volatile("ld.shared.u32 %0, [%1];" : "=r"(v) : "r"(a) : "memory");
    return v;
}
__device__ __forceinline__ void sts128(uint32_t a, float x, float y, float z, float w) {
    asm volatile("st.shared.v4.f32 [%0], {%1,%2,%3,%4};" :: "r"(a), "f"(x), "f"(y), "f"(z), "f"(w) : "memory");
}
__device__ __forceinline__ void sts64(uint32_t a, uint32_t x, uint32_t y) {
    asm volatile("st.shared.v2.u32 [%0], {%1,%2};" :: "r"(a), "r"(x), "r"(y) : "memory");
}
__device__ __forceinline__ void sts32(uint32_t a, uint32_t x) {
    asm volatile("st.shared.u32 [%0], %1;" :: "r"(a), "r"(x) : "memory");
}
__device__ __forceinline__ void sts16(uint32_t a, uint32_t x) {
    asm volatile("st.shared.u16 [%0], %1;" :: "r"(a), "h"((unsigned short)x) : "memory");
}
__device__ __forceinline__ void fma8(float (&acc)[8], float s, const uint4& v) {
    acc[0] = fmaf(s, bf_lo(v.x), acc[0]); acc[1] = fmaf(s, bf_hi(v.x), acc[1]);
    acc[2] = fmaf(s, bf_lo(v.y), acc[2]); acc[3] = fmaf(s, bf_hi(v.y), acc[3]);
    acc[4] = fmaf(s, bf_lo(v.z), acc[4]); acc[5] = fmaf(s, bf_hi(v.z), acc[5]);
    acc[6] = fmaf(s, bf_lo(v.w), acc[6]); acc[7] = fmaf(s, bf_hi(v.w), acc[7]);
}
__device__ __forceinline__ float warp_max(float v) {
    int k = __float_as_int(v);
    k ^= (k >> 31) & 0x7FFFFFFF;
    asm("redux.sync.max.s32 %0, %0, 0xffffffff;" : "+r"(k));
    k ^= (k >> 31) & 0x7FFFFFFF;
    return __int_as_float(k);
}

__device__ __forceinline__ void st_async1(uint32_t a, float x, uint32_t bar) {
    asm volatile("st.async.weak.shared::cluster.mbarrier::complete_tx::bytes.f32 [%0], %1, [%2];" :: "r"(a), "f"(x), "r"(bar) : "memory");
}
__device__ __forceinline__ void st_pub4(void* p, unsigned a, unsigned b, unsigned c, unsigned d) {
    asm volatile("st.relaxed.gpu.global.v4.u32 [%0], {%1,%2,%3,%4};" :: "l"(p), "r"(a), "r"(b), "r"(c), "r"(d) : "memory");
}
__device__ __forceinline__ uint32_t ldg32(const void* p) {
    uint32_t v;
    asm volatile("ld.global.nc.u32 %0, [%1];" : "=r"(v) : "l"(p));
    return v;
}
__device__ __forceinline__ void mma4(float (&c)[4], const uint32_t (&a)[4], uint32_t b0, uint32_t b1) { mma(c, a[0], a[1], a[2], a[3], b0, b1); }
__device__ __forceinline__ float shfl_x(float v, int m) { return __shfl_xor_sync(0xffffffffu, v, m); }
__device__ __forceinline__ unsigned chk(unsigned acc, unsigned w, unsigned tag) {
    unsigned d;
    asm("lop3.b32 %0, %1, %2, %3, 0xF6;" : "=r"(d) : "r"(acc), "r"(w), "r"(tag));
    return d;
}
__device__ __forceinline__ unsigned chk4(unsigned acc, const uint4& v, unsigned tag) { return chk(chk(chk(chk(acc, v.x, tag), v.y, tag), v.z, tag), v.w, tag); }
__device__ __forceinline__ void sts128u(uint32_t a, uint32_t x, uint32_t y, uint32_t z, uint32_t w) {
    asm volatile("st.shared.v4.u32 [%0], {%1,%2,%3,%4};" :: "r"(a), "r"(x), "r"(y), "r"(z), "r"(w) : "memory");
}
__device__ __forceinline__ uint32_t add_bf16x2(uint32_t a, uint32_t b) {
    uint32_t d;
    asm("add.rn.bf16x2 %0, %1, %2;" : "=r"(d) : "r"(a & ~1u), "r"(b & ~1u));
    return d;
}
__device__ __forceinline__ void spin_until(unsigned t) { while ((int)(clock32() - t) < 0) {} }
__device__ __forceinline__ uint32_t fma_bf16x2(uint32_t a, uint32_t b, uint32_t c) {
    uint32_t d;
    asm("fma.rn.bf16x2 %0, %1, %2, %3;" : "=r"(d) : "r"(a), "r"(b), "r"(c));
    return d;
}
__device__ __forceinline__ uint32_t mul_bf16x2(uint32_t a, uint32_t b) {
    uint32_t d;
    asm("mul.rn.bf16x2 %0, %1, %2;" : "=r"(d) : "r"(a), "r"(b));
    return d;
}
__device__ __forceinline__ bool mbar_test(uint32_t bar) {
    uint32_t ok;
    asm volatile("{.reg .pred p; mbarrier.test_wait.parity.shared::cta.b64 p, [%1], 0; selp.u32 %0,1,0,p;}" : "=r"(ok) : "r"(bar) : "memory");
    return __all_sync(0xffffffffu, ok);
}
__device__ __forceinline__ uint4 ld_home4(const void* p) {
    uint4 v;
    asm volatile("{.reg .b128 d, z; .reg .b64 lo, hi; mov.b64 lo, 0; mov.b128 z, {lo, lo};"
                 " atom.relaxed.gpu.global.cas.b128 d, [%4], z, z; mov.b128 {lo, hi}, d; mov.b64 {%0,%1}, lo; mov.b64 {%2,%3}, hi;}"
                 : "=r"(v.x), "=r"(v.y), "=r"(v.z), "=r"(v.w) : "l"(p) : "memory");
    return v;
}
__device__ __forceinline__ uint2 ld_home2(const void* p) {
    uint2 v;
    asm volatile("{.reg .b64 a; atom.relaxed.gpu.global.or.b64 a, [%2], 0; mov.b64 {%0,%1}, a;}" : "=r"(v.x), "=r"(v.y) : "l"(p) : "memory");
    return v;
}
#define PIN(x) asm volatile("" : "+r"(x))
#define PINL(x) asm volatile("" : "+l"(x))

__global__ void __cluster_dims__(2, 1, 1) __launch_bounds__(NTHREADS, 1)
fused_kernel(const __grid_constant__ Params P)
{
    extern __shared__ __align__(1024) unsigned char smem_raw[];
    const int tid = threadIdx.x;
    const int cl = blockIdx.x >> 1;
    const int r = blockIdx.x & 1;
    const uint32_t sm = (uint32_t)__cvta_generic_to_shared(smem_raw);
    uint4 wv[10];
    uint32_t xw[5];
    if (tid < 256) {
        asm volatile("barrier.cluster.arrive.relaxed.aligned;" ::: "memory");
        const int m0 = 320 * r + 10 * (tid >> 3);
        const __nv_bfloat16* wp = P.wq + (size_t)m0 * 4096 + cl * 64 + (tid & 7) * 8;
#pragma unroll
        for (int i = 0; i < 10; i++) wv[i] = ldg_stream(wp + i * 4096);
#pragma unroll
        for (int i = 0; i < 5; i++) xw[i] = ldg32(P.x + m0 + 2 * i);
    }
    unsigned t0 = 0;
    if (tid >= 256) t0 = gtimer();
    if (tid == 256) {
#pragma unroll
        for (int i = 0; i < B_CKV; i++) asm volatile("mbarrier.init.shared::cta.b64 [%0], 1;" :: "r"(sm + SM_BAR + 8 * i) : "memory");
#pragma unroll
        for (int i = 0; i < B_CKV; i++) asm volatile("mbarrier.arrive.expect_tx.shared::cta.b64 _, [%0], 8192;" :: "r"(sm + SM_BAR + 8 * i) : "memory");
        asm volatile("fence.mbarrier_init.release.cluster;" ::: "memory");
    }
    const int pu = cl < 36 ? cl - 4 : cl - 36, pn = cl < 36 ? 8 : 7;
    const int pv = pu >= 2 * pn ? pu - 2 * pn : pu;
    const int lc = cl < 4 ? cl : cl - pv + (pv >= pn ? 2 * (pv - pn) + 1 : 2 * pv);
    const int b = 2 * lc + r;
    const int h = b >> 2;
    const int pp = lc & 1;
    const int warp = tid >> 5, lane = tid & 31;
    const bool ffn = h < 27;
    Scratch* const S = P.s;

    if (warp < 8) {
        const int g = lane >> 2, t = lane & 3, l7 = lane & 7;
        const int kq = warp >> 1, nh = warp & 1;
        const uint32_t smp = mapa(sm, r ^ 1);
        const int row1 = 2 * l7 + ((lane >> 3) & 1);
        uint32_t a_wuk = sm + SM_WUK + (32 * warp + row1) * 128 + (((lane >> 4) ^ (row1 & 7)) << 4);
        unsigned* p_e2w = reinterpret_cast<unsigned*>(S->e2) + (((cl & 1) * 32 + (cl >> 1)) * 2 + r) * (4 * 32) + 16 * warp + 8 * (t & 1) + g;
        const uint4* p_e2r = S->e2 + ((16 * pp + (tid >> 4)) * 2 + r) * 32 + (tid & 15);
        uint32_t a_qsw = sm + SM_QS + (tid >> 4) * 512 + (((tid & 15) ^ ((tid >> 4) & 7)) << 4);
        uint32_t a_qsr = sm + SM_QS + (lane & 15) * 512 + (((lane >> 4) ^ l7) << 4);
        uint32_t a_s = sm + SM_CKV + (16 * warp + l7) * 128 + (((lane >> 3) ^ l7) << 4);
        uint32_t o_spw = warp * 1024 + ((lane ^ (nh << 2)) << 4);
        uint32_t a_ct = sm + SM_CKV + kq * 16384 + lane * 128 + (((4 * nh) ^ l7) << 4);
        uint32_t a_sr = sm + g * 1024 + ((warp ^ (g & 1)) << 6) + t * 16;
        uint2* p_stw = S->st + (16 * pp + 8 * r + warp) * 128 + h * 4 + lane;
        uint4* p_e3w = S->e3 + ((((16 * pp + g) * 2 + r) * 8 + warp) * 32 + h) * 4 + t;
        const uint4* p_e3r = S->e3 + ((h * 2 + r) * 8 + warp) * 128 + lane;
        const int krow = l7 + 8 * (lane >> 4), csel = (lane >> 3) & 1;
        uint32_t a_w1 = sm + SM_W1 + (80 * kq + krow) * 64 + (((2 * nh + csel) ^ (l7 >> 1)) << 4);
        uint32_t a_wuv = sm + SM_WUV + (32 * warp + krow) * 128 + ((csel ^ l7) << 4);
        uint32_t a_fin[5];
#pragma unroll
        for (int i = 0; i < 5; i++) {
            const int N = 10 * (warp & 3) + 2 * i + csel;
            a_fin[i] = sm + (warp >> 2) * 10240 + (N >> 3) * 2048 + krow * 128 + (((N & 7) ^ l7) << 4);
            PIN(a_fin[i]);
        }
        uint32_t b_xc = ((t >> 1) == r ? mapa(sm, r) : smp), b_xh = (nh == r ? mapa(sm, r) : smp);
        uint32_t a_xc = b_xc + SM_XC + (8 * r + warp) * 128 + ((t & 1) * 8 + g) * 8;
        uint32_t a_xh = b_xh + SM_XH + ((t & 1) * 8 + g) * 32 + (4 * r + kq) * 4;
        unsigned* p_e4w = reinterpret_cast<unsigned*>(S->e4) + (10 * warp + t) * (4 * 256) + b * 8 + g;
        PIN(a_wuk); PINL(p_e2w); PINL(p_e2r); PIN(a_s); PIN(a_qsw); PIN(a_qsr); PIN(o_spw); PIN(a_ct); PIN(a_sr);
        PINL(p_stw); PINL(p_e3w); PINL(p_e3r); PIN(a_w1); PIN(a_wuv); PIN(a_xc); PIN(a_xh); PINL(p_e4w);

        {
            float acc[8];
#pragma unroll
            for (int e = 0; e < 8; e++) acc[e] = 0.f;
#pragma unroll
            for (int i = 0; i < 10; i++) fma8(acc, (i & 1) ? bf_hi(xw[i >> 1]) : bf_lo(xw[i >> 1]), wv[i]);
            const bool b4 = lane & 16, b3 = lane & 8;
            float k4[4], k2[2];
#pragma unroll
            for (int e = 0; e < 4; e++) k4[e] = (b4 ? acc[4 + e] : acc[e]) + shfl_x(b4 ? acc[e] : acc[4 + e], 16);
#pragma unroll
            for (int e = 0; e < 2; e++) k2[e] = (b3 ? k4[2 + e] : k4[e]) + shfl_x(b3 ? k4[e] : k4[2 + e], 8);
            asm volatile("barrier.cluster.wait.aligned;" ::: "memory");
            const uint32_t o = SM_XQ + (8 * r + warp) * 256 + (4 * l7 + (lane >> 3)) * 8;
            const uint32_t smo = mapa(sm, r);
            st_async2(smp + o, __float_as_uint(k2[0]), __float_as_uint(k2[1]), smp + SM_BAR + 8 * B_XQ);
            st_async2(smo + o, __float_as_uint(k2[0]), __float_as_uint(k2[1]), smo + SM_BAR + 8 * B_XQ);
        }
        bar_sync(1, 288);
        const unsigned tag = lds32(sm + SM_G + 4);
        t0 = lds32(sm + SM_G + 12);
        {
            mbar_wait(sm + SM_BAR + 8 * B_XQ);
            float2 qv[16];
#pragma unroll
            for (int i = 0; i < 16; i++) qv[i] = lds64f(sm + SM_XQ + i * 256 + lane * 8);
#pragma unroll
            for (int i = 0; i < 8; i++) { qv[i].x += qv[i + 8].x; qv[i].y += qv[i + 8].y; }
#pragma unroll
            for (int i = 0; i < 4; i++) { qv[i].x += qv[i + 4].x; qv[i].y += qv[i + 4].y; }
            qv[0].x = (qv[0].x + qv[2].x) + (qv[1].x + qv[3].x);
            qv[0].y = (qv[0].y + qv[2].y) + (qv[1].y + qv[3].y);
            const uint32_t qw = pack_bf16(qv[0].x, qv[0].y);
            uint32_t qb[8];
#pragma unroll
            for (int i = 0; i < 8; i++) qb[i] = __shfl_sync(0xffffffffu, qw, 4 * i + t);
            STAMP(1);
            mbar_wait(sm + SM_BAR + 8 * (B_WUK + kq));
            uint32_t a[8][4];
#pragma unroll
            for (int s = 0; s < 8; s++) ldsm4((a_wuk ^ ((s & 3) << 5)) + (s >> 2) * 2048, a[s]);
            float c[4][4];
#pragma unroll
            for (int i = 0; i < 4; i++) {
                c[i][0] = c[i][1] = c[i][2] = c[i][3] = 0.f;
                mma4(c[i], a[2 * i], qb[4 * (i & 1)], qb[4 * (i & 1) + 1]);
            }
#pragma unroll
            for (int i = 0; i < 4; i++) mma4(c[i], a[2 * i + 1], qb[4 * (i & 1) + 2], qb[4 * (i & 1) + 3]);
            const float sc = 0.08838834764831845f * 1.4426950408889634f;
            const float lo = ((t & 1) ? c[2][0] + c[3][0] : c[0][0] + c[1][0]) * sc;
            const float hi = ((t & 1) ? c[2][2] + c[3][2] : c[0][2] + c[1][2]) * sc;
            const uint32_t lob = (lo != lo) ? 0x7FFEu : (((__float_as_uint(lo) + 0x10000u) >> 16) & 0xFFFEu);
            if (t < 2) st_pub1(p_e2w, (pack_bf16(0.f, hi) & 0xFFFF0000u) | lob | tag);
        }
        STAMP(2);
        {
            bar_sync(3, 256);
            float s[4][4];
#pragma unroll
            for (int i = 0; i < 4; i++) s[i][0] = s[i][1] = s[i][2] = s[i][3] = 0.f;
            uint32_t ct[4][4][4];
            uint32_t bf[2][4][4];
            uint4 v[4];
#define LOAD_BF(q) _Pragma("unroll") for (int i = 0; i < 4; i++) ldsm4((a_s ^ ((i >> 1) << 6)) + (q) * 16384 + (i & 1) * 1024, bf[(q) & 1][i])
#define LOAD_CT()  _Pragma("unroll") for (int i = 0; i < 16; i++) ldsm4t((a_ct ^ ((i >> 2) << 4)) + (i & 3) * 4096, ct[i >> 2][i & 3])
#define STAGE_Q(st2) do { \
                int it = 0; \
                while ((chk4(chk4(0u, v[2 * (st2)], tag), v[2 * (st2) + 1], tag) & 1u) && ++it < SPIN_MAX) { \
                    v[2 * (st2)] = ld_home4(p_e2r + (st2) * 16); \
                    v[2 * (st2) + 1] = ld_home4(p_e2r + (st2) * 16 + 64 * 32); \
                } \
                COUNT(26 + st2, it); \
                const uint4 &x = v[2 * (st2)], &y = v[2 * (st2) + 1]; \
                sts128u(a_qsw + (st2) * 256, add_bf16x2(x.x, y.x), add_bf16x2(x.y, y.y), add_bf16x2(x.z, y.z), add_bf16x2(x.w, y.w)); \
            } while (0)
#define LOAD_QA(q) _Pragma("unroll") for (int i = 0; i < 4; i++) ldsm4((a_qsr ^ (i << 5)) + (q) * 128, qa[(q) & 1][i])
#define S_BLOCK(q) do { \
                const uint32_t (&A)[4][4] = qa[(q) & 1]; const uint32_t (&B)[4][4] = bf[(q) & 1]; \
                mma4(s[0], A[0], B[0][0], B[0][1]); mma4(s[1], A[0], B[1][0], B[1][1]); \
                mma4(s[2], A[1], B[0][2], B[0][3]); mma4(s[3], A[1], B[1][2], B[1][3]); \
                mma4(s[0], A[2], B[2][0], B[2][1]); mma4(s[1], A[2], B[3][0], B[3][1]); \
                mma4(s[2], A[3], B[2][2], B[2][3]); mma4(s[3], A[3], B[3][2], B[3][3]); \
            } while (0)
            uint32_t qa[2][4][4];
            while (gtimer() - t0 < P.ta) {}
            v[0] = ld_poll4(p_e2r);
            v[1] = ld_poll4(p_e2r + 64 * 32);
            mbar_wait(sm + SM_BAR + 8 * (B_CKV + 0));
            LOAD_BF(0);
            STAGE_Q(0);
            while (gtimer() - t0 < P.tb) {}
            v[2] = ld_poll4(p_e2r + 16);
            v[3] = ld_poll4(p_e2r + 16 + 64 * 32);
            mbar_wait(sm + SM_BAR + 8 * (B_CKV + 1));
            LOAD_BF(1);
            bar_sync(3, 256);
            LOAD_QA(0);
            LOAD_QA(1);
            S_BLOCK(0);
            S_BLOCK(1);
            if (kq < 2) { LOAD_CT(); }
            mbar_wait(sm + SM_BAR + 8 * (B_CKV + 2));
            LOAD_BF(2);
            STAGE_Q(1);
            bar_sync(3, 256);
            LOAD_QA(2);
            LOAD_QA(3);
            mbar_wait(sm + SM_BAR + 8 * (B_CKV + 3));
            STAMP(4);
            LOAD_BF(3);
            S_BLOCK(2);
            S_BLOCK(3);
            {
                const float u0 = s[0][0] + s[2][0], u1 = s[0][1] + s[2][1], u2 = s[1][0] + s[3][0], u3 = s[1][1] + s[3][1];
                const float v0 = s[0][2] + s[2][2], v1 = s[0][3] + s[2][3], v2 = s[1][2] + s[3][2], v3 = s[1][3] + s[3][3];
                st_async4(smp + SM_SPR + o_spw, u0, u1, u2, u3, smp + SM_BAR + 8 * B_SP);
                st_async4(smp + SM_SPR + 512 + o_spw, v0, v1, v2, v3, smp + SM_BAR + 8 * B_SP);
                sts128(sm + SM_SPL + o_spw, u0, u1, u2, u3);
                sts128(sm + SM_SPL + 512 + o_spw, v0, v1, v2, v3);
            }
            if (kq >= 2) { LOAD_CT(); }
            bar_sync(2, 288);
            {
                const uint4 ul = lds128(a_sr + SM_SPL), vl = lds128(a_sr + SM_SPL + 512);
                mbar_wait(sm + SM_BAR + 8 * B_SP);
                STAMP(6);
                const uint4 ur = lds128(a_sr + SM_SPR), vr = lds128(a_sr + SM_SPR + 512);
                const float u0 = __uint_as_float(ul.x) + __uint_as_float(ur.x), u1 = __uint_as_float(ul.y) + __uint_as_float(ur.y);
                const float u2 = __uint_as_float(ul.z) + __uint_as_float(ur.z), u3 = __uint_as_float(ul.w) + __uint_as_float(ur.w);
                const float v0 = __uint_as_float(vl.x) + __uint_as_float(vr.x), v1 = __uint_as_float(vl.y) + __uint_as_float(vr.y);
                const float v2 = __uint_as_float(vl.z) + __uint_as_float(vr.z), v3 = __uint_as_float(vl.w) + __uint_as_float(vr.w);
                const float mu = warp_max(fmaxf(fmaxf(u0, u1), fmaxf(u2, u3)));
                const float mv = warp_max(fmaxf(fmaxf(v0, v1), fmaxf(v2, v3)));
                const uint32_t a0 = pack_bf16(ex2(u0 - mu), ex2(u1 - mu)), a2 = pack_bf16(ex2(u2 - mu), ex2(u3 - mu));
                const uint32_t a1 = pack_bf16(ex2(v0 - mv), ex2(v1 - mv)), a3 = pack_bf16(ex2(v2 - mv), ex2(v3 - mv));
                sts128u(sm + SM_P + g * 512 + warp * 64 + t * 16, a0, a1, a2, a3);
                bar_sync(3, 256);
                uint4 pa[8];
#pragma unroll
                for (int q = 0; q < 8; q++) pa[q] = lds128(sm + SM_P + q * 512 + lane * 16);
                float o[2][4][4];
#pragma unroll
                for (int n = 0; n < 4; n++)
#pragma unroll
                    for (int e = 0; e < 4; e++) o[0][n][e] = o[1][n][e] = 0.f;
#pragma unroll
                for (int i = 0; i < 4; i++) {
#pragma unroll
                    for (int n = 0; n < 4; n++) mma(o[0][n], pa[2 * i].x, pa[2 * i].y, pa[2 * i].z, pa[2 * i].w, ct[n][i][0], ct[n][i][1]);
#pragma unroll
                    for (int n = 0; n < 4; n++) mma(o[1][n], pa[2 * i + 1].x, pa[2 * i + 1].y, pa[2 * i + 1].z, pa[2 * i + 1].w, ct[n][i][2], ct[n][i][3]);
                }
                const uint32_t q0 = r ? a1 : a0, q1 = r ? a3 : a2;
                float l = (bf_lo(q0) + bf_hi(q0)) + (bf_lo(q1) + bf_hi(q1));
#pragma unroll
                for (int d = 1; d < 32; d <<= 1) l += shfl_x(l, d);
                if (lane == 0) st_pub64(p_stw, tagf(l, tag), __float_as_uint(r ? mv : mu));
                uint32_t w0[4], w1[4];
#pragma unroll
                for (int n = 0; n < 4; n++) {
                    w0[n] = pack_bf16(o[0][n][0] + o[1][n][0], o[0][n][1] + o[1][n][1]);
                    w1[n] = pack_bf16(o[0][n][2] + o[1][n][2], o[0][n][3] + o[1][n][3]);
                }
                st_pub2x64(p_e3w, tagw(w0[0], tag), w0[1], tagw(w0[2], tag), w0[3]);
                st_pub2x64(p_e3w + 8 * 2 * 8 * 32 * 4, tagw(w1[0], tag), w1[1], tagw(w1[2], tag), w1[3]);
            }
        }
        STAMP(8);
        if (ffn) {
            const uint32_t xa = sm + SM_XS + 160 * kq + 4 * t;
            uint32_t xb[5][2];
#pragma unroll
            for (int s = 0; s < 5; s++) { xb[s][0] = lds32(xa + s * 32); xb[s][1] = lds32(xa + s * 32 + 16); }
            mbar_wait(sm + SM_BAR + 8 * (B_W1 + (warp >> 2)));
            uint32_t aw[5][4];
#pragma unroll
            for (int s = 0; s < 5; s++) ldsm4t(a_w1 + s * 1024, aw[s]);
            float c0[4] = {0.f, 0.f, 0.f, 0.f}, c1[4] = {0.f, 0.f, 0.f, 0.f};
#pragma unroll
            for (int s = 0; s < 5; s++) mma4((s & 1) ? c1 : c0, aw[s], xb[s][0], xb[s][1]);
            if (t < 2) st_async1(a_xh, t ? c0[2] + c1[2] : c0[0] + c1[0], b_xh + SM_BAR + 8 * B_XH);
        }
        float invl;
        {
            uint32_t a[8][4];
            uint4 v[4];
            uint32_t fw[4];
            int it = 0;
            bar_sync(4, 288);
            {
                const unsigned tq = lds32(sm + SM_G + 16);
                while ((int)(gtimer() - tq) < 0) {}
            }
#pragma unroll
            for (int i = 0; i < 4; i++) v[i] = ld_poll2x64(p_e3r + i * 32);
            STAMP(24);
            if (ffn && warp == 0) {
                mbar_wait(sm + SM_BAR + 8 * B_XH);
                const uint4 u = lds128(sm + SM_XH + (lane & 15) * 32), y = lds128(sm + SM_XH + (lane & 15) * 32 + 16);
                float hv = ((__uint_as_float(u.x) + __uint_as_float(u.y)) + (__uint_as_float(u.z) + __uint_as_float(u.w))) +
                           ((__uint_as_float(y.x) + __uint_as_float(y.y)) + (__uint_as_float(y.z) + __uint_as_float(y.w)));
                hv = bf_lo(pack_bf16(hv, 0.f));
                hv = __fdividef(hv, 1.f + __expf(-hv)) * (1.f - __uint_as_float(lds32(sm + SM_G)));
                if (lane < 16) st_pub1(reinterpret_cast<unsigned*>(S->eh) + 16 * b + 2 * (lane & 6) + 2 * (lane >> 3) + (lane & 1), tagf(hv, tag));
            }
            mbar_wait(sm + SM_BAR + 8 * (B_WUV + kq));
#pragma unroll
            for (int i = 0; i < 8; i++) ldsm4t((a_wuv ^ ((i >> 1) << 5)) + (i & 1) * 2048, a[i]);
            bar_sync(6, 288);
#pragma unroll
            for (int i = 0; i < 4; i++) fw[i] = lds32(sm + SM_F + (8 * i + g) * 4);
            invl = __uint_as_float(lds32(sm + SM_G + 8));
            while (true) {
                unsigned bad = 0u;
#pragma unroll
                for (int i = 0; i < 4; i++) bad = chk(chk(bad, v[i].x, tag), v[i].z, tag);
                if (!(bad & 1u) || ++it >= SPIN_MAX) break;
#pragma unroll
                for (int i = 0; i < 4; i++) v[i] = ld_home4(p_e3r + i * 32);
            }
            COUNT(28, it);
            __syncwarp();
            STAMP(10);
            uint32_t bx = mul_bf16x2(fw[0], v[0].x & ~1u), by = mul_bf16x2(fw[0], v[0].y), bz = mul_bf16x2(fw[0], v[0].z & ~1u), bw = mul_bf16x2(fw[0], v[0].w);
#pragma unroll
            for (int i = 1; i < 4; i++) {
                bx = fma_bf16x2(fw[i], v[i].x & ~1u, bx); by = fma_bf16x2(fw[i], v[i].y, by);
                bz = fma_bf16x2(fw[i], v[i].z & ~1u, bz); bw = fma_bf16x2(fw[i], v[i].w, bw);
            }
            float c[4][4];
#pragma unroll
            for (int i = 0; i < 4; i++) {
                c[i][0] = c[i][1] = c[i][2] = c[i][3] = 0.f;
                mma4(c[i], a[2 * i], bx, by);
            }
#pragma unroll
            for (int i = 0; i < 4; i++) mma4(c[i], a[2 * i + 1], bz, bw);
            float e[8], k4[4];
#pragma unroll
            for (int i = 0; i < 4; i++) { e[2 * i] = c[i][0] + c[i][1]; e[2 * i + 1] = c[i][2] + c[i][3]; }
            const bool t1 = t & 2, t0 = t & 1;
#pragma unroll
            for (int i = 0; i < 4; i++) k4[i] = (t1 ? e[4 + i] : e[i]) + shfl_x(t1 ? e[i] : e[4 + i], 2);
            const float k0 = (t0 ? k4[2] : k4[0]) + shfl_x(t0 ? k4[0] : k4[2], 1);
            const float k1 = (t0 ? k4[3] : k4[1]) + shfl_x(t0 ? k4[1] : k4[3], 1);
            st_async2(a_xc, __float_as_uint(k0), __float_as_uint(k1), b_xc + SM_BAR + 8 * B_XC);
        }
        const bool red = b < 80;
        const uint4* p_eh = S->eh + (27 * r + min(warp + 4 * g, 26)) * 8 + t;
        uint4 hv0, hv1;
        if (red && warp < 4) { hv0 = ld_poll4(p_eh); hv1 = ld_poll4(p_eh + 4); }
        {
            float c[5][4];
#pragma unroll
            for (int i = 0; i < 5; i++) c[i][0] = c[i][1] = c[i][2] = c[i][3] = 0.f;
            const int half = warp >> 2;
            const float gt = __uint_as_float(lds32(sm + SM_G));
            uint32_t wa[2][5][4];
            mbar_wait(sm + SM_BAR + 8 * (B_WO + half));
#pragma unroll
            for (int i = 0; i < 5; i++) ldsm4t(a_fin[i] + SM_WO, wa[0][i]);
            const bool early = mbar_test(sm + SM_BAR + 8 * (B_WO + 2 + half));
            if (early) {
#pragma unroll
                for (int i = 0; i < 5; i++) ldsm4t(a_fin[i] + SM_WO + 20480, wa[1][i]);
            }
            mbar_wait(sm + SM_BAR + 8 * B_XC);
            STAMP(13);
            float xv[16];
#pragma unroll
            for (int i = 0; i < 16; i++) xv[i] = __uint_as_float(lds32(sm + SM_XC + i * 128 + lane * 4));
#pragma unroll
            for (int i = 0; i < 8; i++) xv[i] += xv[i + 8];
            const float cv = (((xv[0] + xv[4]) + (xv[1] + xv[5])) + ((xv[2] + xv[6]) + (xv[3] + xv[7]))) * (gt * invl);
            const uint32_t w = pack_bf16(cv, shfl_x(cv, 2));
            uint32_t bb[4];
#pragma unroll
            for (int q = 0; q < 4; q++) bb[q] = __shfl_sync(0xffffffffu, w, (q >> 1) * 16 + 4 * t + (q & 1));
#pragma unroll
            for (int i = 0; i < 5; i++) mma4(c[i], wa[0][i], bb[0], bb[1]);
            if (!early) {
                mbar_wait(sm + SM_BAR + 8 * (B_WO + 2 + half));
#pragma unroll
                for (int i = 0; i < 5; i++) ldsm4t(a_fin[i] + SM_WO + 20480, wa[1][i]);
            }
#pragma unroll
            for (int i = 0; i < 5; i++) mma4(c[i], wa[1][i], bb[2], bb[3]);
            const bool t0 = t & 1, t1 = t & 2;
            const float v0 = t1 ? (t0 ? c[1][2] : c[1][0]) : (t0 ? c[0][2] : c[0][0]);
            const float v1 = t1 ? (t0 ? c[3][2] : c[3][0]) : (t0 ? c[2][2] : c[2][0]);
            const float v2 = t0 ? c[4][2] : c[4][0];
            st_pub1(p_e4w, tagf(v0, tag));
            st_pub1(p_e4w + 4 * 4 * 256, tagf(v1, tag));
            if (!t1) st_pub1(p_e4w + 8 * 4 * 256, tagf(v2, tag));
        }
        STAMP(15);
        if (red) {
            if (warp < 4) {
                int it = 0;
                while (((chk4(0u, hv0, tag) | chk4(0u, hv1, tag)) & 1u) && ++it < SPIN_MAX) { hv0 = ld_home4(p_eh); hv1 = ld_home4(p_eh + 4); }
                __syncwarp();
                const bool ok = warp + 4 * g < 27;
                const uint32_t w0 = ok ? pack_bf16(untagf(hv0.x), untagf(hv0.y)) : 0u, w1 = ok ? pack_bf16(untagf(hv0.z), untagf(hv0.w)) : 0u;
                const uint32_t w2 = ok ? pack_bf16(untagf(hv1.x), untagf(hv1.y)) : 0u, w3 = ok ? pack_bf16(untagf(hv1.z), untagf(hv1.w)) : 0u;
                uint32_t hb[14][2];
#pragma unroll
                for (int i = 0; i < 7; i++) {
                    hb[2 * i][0] = __shfl_sync(0xffffffffu, w0, 4 * i + t); hb[2 * i][1] = __shfl_sync(0xffffffffu, w1, 4 * i + t);
                    hb[2 * i + 1][0] = __shfl_sync(0xffffffffu, w2, 4 * i + t); hb[2 * i + 1][1] = __shfl_sync(0xffffffffu, w3, 4 * i + t);
                }
                const uint32_t a_w2 = sm + SM_W2 + (32 * warp + krow) * 32 + ((csel ^ (l7 >> 2)) << 4);
                const uint32_t a_w2l = a_w2 + (warp < 3 ? 6 * 4096 : 0);
                const uint32_t b_fb = ((t & 1) == r ? mapa(sm, r) : smp);
                mbar_wait(sm + SM_BAR + 8 * B_W2);
                uint32_t a[14][4];
#pragma unroll
                for (int i = 0; i < 12; i++) ldsm4t(a_w2 + (i >> 1) * 4096 + (i & 1) * 512, a[i]);
                ldsm4t(a_w2l, a[12]);
                ldsm4t(a_w2l + 512, a[13]);
                float c[4][4];
#pragma unroll
                for (int i = 0; i < 4; i++) c[i][0] = c[i][1] = c[i][2] = c[i][3] = 0.f;
#pragma unroll
                for (int i = 0; i < 14; i++) mma4(c[i & 3], a[i], hb[i][0], hb[i][1]);
                const float e = (t & 1) ? (c[0][2] + c[1][2]) + (c[2][2] + c[3][2]) : (c[0][0] + c[1][0]) + (c[2][0] + c[3][0]);
                if (t < 2) st_async1(b_fb + SM_FIN + g * 48 + 16 + (4 * r + warp) * 4, e, b_fb + SM_BAR + 8 * B_FB);
                STAMP(16);
            } else {
                const uint4* p = S->e4 + b * 256 + (tid - 128);
                spin_until(clock32() + P.d4);
                uint4 u, v;
                int it = 0;
                do { u = ld_poll4(p); v = ld_poll4(p + 128); } while (((chk4(0u, u, tag) | chk4(0u, v, tag)) & 1u) && ++it < SPIN_MAX);
                COUNT(29, it);
                __syncwarp();
                STAMP(17);
                const float s0 = untagf(u.x) + untagf(v.x), s1 = untagf(u.y) + untagf(v.y), s2 = untagf(u.z) + untagf(v.z), s3 = untagf(u.w) + untagf(v.w);
                const bool b4 = lane & 16, b3 = lane & 8;
                const float k0 = (b4 ? s2 : s0) + shfl_x(b4 ? s0 : s2, 16);
                const float k1 = (b4 ? s3 : s1) + shfl_x(b4 ? s1 : s3, 16);
                float s = (b3 ? k1 : k0) + shfl_x(b3 ? k0 : k1, 8);
                s += shfl_x(s, 4);
                s += shfl_x(s, 2);
                if (!(lane & 6)) sts32(sm + SM_FIN + ((lane & 1) * 4 + (lane >> 3)) * 48 + (warp - 4) * 4, __float_as_uint(s));
                bar_sync(7, 128);
            }
            if (warp == 4 && lane < 8) {
                mbar_wait(sm + SM_BAR + 8 * B_FB);
                float o[3];
#pragma unroll
                for (int i = 0; i < 3; i++) {
                    const uint4 u = lds128(sm + SM_FIN + lane * 48 + i * 16);
                    o[i] = (__uint_as_float(u.x) + __uint_as_float(u.y)) + (__uint_as_float(u.z) + __uint_as_float(u.w));
                }
                P.out[b * 8 + lane] = __float2bfloat16((o[1] + o[2]) + o[0]);
                if (b == 0 && lane == 0) st_pub1(&S->epoch, tag);
            }
        }
    } else if (warp == 8) {
        __syncwarp();
        asm volatile("barrier.cluster.arrive.relaxed.aligned;" ::: "memory");
        if (lane < 6) asm volatile("prefetch.tensormap [%0];" :: "l"(&P.m[lane]) : "memory");
        const int k = lane;
        const uint32_t bar = sm + SM_BAR + 8 * min(k, B_W2);
        int map, c0 = 0, c1, c2;
        uint32_t dst, due;
        bool pending = true;
        if (k < B_CKV)      { map = 0; c1 = 256 * r + 64 * k;                c2 = cl;                dst = SM_WUK + k * 8192; }
        else if (k < B_W1)  { map = 1; c1 = 128 * h;                         c2 = 4 * r + k - B_CKV; dst = SM_CKV + (k - B_CKV) * 16384; }
        else if (k < B_WUV) { map = 2; c1 = 320 * r + 160 * (k - B_W1);      c2 = h; c0 = 32 * pp;   dst = SM_W1 + (k - B_W1) * 10240; pending = ffn; }
        else if (k < B_WO)  { map = 3; c1 = 256 * r + 64 * (k - B_WUV);      c2 = lc;                dst = SM_WUV + (k - B_WUV) * 8192; }
        else if (k < B_W2)  { map = 4; c1 = 32 * b + 16 * ((k - B_WO) >> 1); c2 = 5 * (k & 1);       dst = SM_WO + (k - B_WO) * 10240; }
        else                { map = 5; c1 = 864 * r + 216 * (k - B_W2);      c2 = lc >> 2; c0 = 16 * (lc & 3); dst = SM_W2 + (k - B_W2) * 6912; pending = b < 80 && k < NCHUNK; }
        const bool mine = pending;
        due = P.due[k] + ((b * 37) & 127) * P.stag[k] / 128;
        int lim = B_CKV;
        while (__any_sync(0xffffffffu, pending)) {
            if (!__any_sync(0xffffffffu, pending && k < lim)) {
                if (lim == B_CKV) { bar_sync(5, 64); lim = B_W2; }
                else { mbar_wait(sm + SM_BAR + 8 * B_DEAD); lim = NCHUNK; }
            }
            if (pending && k < lim && gtimer() - t0 >= due) {
                asm volatile("cp.async.bulk.tensor.3d.shared::cluster.global.mbarrier::complete_tx::bytes [%0], [%1, {%3,%4,%5}], [%2];"
                             :: "r"(sm + dst), "l"(&P.m[map]), "r"(bar), "r"(c0), "r"(c1), "r"(c2) : "memory");
                pending = false;
            }
        }
        if (mine && k >= B_WO) mbar_wait(bar);
        __syncwarp();
        STAMP(22);
    } else {
        const unsigned old = ld_poll1(&S->epoch) & 1u;
        uint32_t xv[10], gw[10];
#pragma unroll
        for (int i = 0; i < 10; i++) {
            xv[i] = ldg32(P.x + (i * 32 + lane) * 2);
            gw[i] = ldg32(P.gate + (i * 32 + lane) * 2);
        }
        if (lane == 0) {
#pragma unroll
            for (int i = B_CKV; i < NBAR; i++) asm volatile("mbarrier.init.shared::cta.b64 [%0], 1;" :: "r"(sm + SM_BAR + 8 * i) : "memory");
#pragma unroll
            for (int i = B_CKV; i < B_DEAD; i++) {
                const uint32_t tx = i < B_W1 ? 16384 : i < B_WUV ? 10240 : i < B_WO ? 8192 : i < B_W2 ? 10240 : i == B_W2 ? 27648 :
                                    i == B_SP ? 8192 : i == B_XC ? 2048 : i == B_XQ ? 4096 : i == B_FB ? 256 : 512;
                asm volatile("mbarrier.arrive.expect_tx.shared::cta.b64 _, [%0], %1;" :: "r"(sm + SM_BAR + 8 * i), "r"(tx) : "memory");
            }
            asm volatile("fence.mbarrier_init.release.cluster;" ::: "memory");
        }
        __syncwarp();
        asm volatile("barrier.cluster.arrive.relaxed.aligned;" ::: "memory");
        bar_arrive(5, 64);
        st_pub4(S->e2 + (((cl & 1) * 32 + (cl >> 1)) * 2 + r) * 32 + lane, old, old, old, old);
        st_pub64(S->st + (16 * pp + 8 * r + (lane >> 2)) * 128 + h * 4 + (lane & 3), old, 0u);
        if (lane == 0) { sts32(sm + SM_G + 4, old ^ 1u); sts32(sm + SM_G + 12, t0); }
#pragma unroll
        for (int i = 0; i < 5; i++) st_pub4(&S->e4[(i * 16 + (lane >> 1)) * 256 + b * 2 + (lane & 1)], old, old, old, old);
        float z = 0.f;
#pragma unroll
        for (int i = 0; i < 10; i++) {
            if ((i >= 5) == (r != 0)) sts32(sm + SM_XS + ((i % 5) * 32 + lane) * 4, xv[i]);
            z = fmaf(bf_lo(xv[i]), bf_lo(gw[i]), z);
            z = fmaf(bf_hi(xv[i]), bf_hi(gw[i]), z);
        }
#pragma unroll
        for (int d = 1; d < 32; d <<= 1) z += shfl_x(z, d);
        if (lane == 0) sts32(sm + SM_G, __float_as_uint(__fdividef(1.f, 1.f + __expf(-z))));
        bar_arrive(1, 288);
        {
            bar_sync(2, 288);
            if (lane == 0) asm volatile("mbarrier.arrive.shared::cta.b64 _, [%0];" :: "r"(sm + SM_BAR + 8 * B_DEAD) : "memory");
            mbar_wait(sm + SM_BAR + 8 * B_SP);
            const unsigned now = gtimer();
            if (lane < 8) st_pub64(S->st + (16 * pp + 8 * r + lane) * 128 + h * 4 + 1, (now & ~1u) | (old ^ 1u), 0u);
            const uint2* p_str = S->st + h * 128 + lane * 4;
            while (gtimer() - now < P.d3) {}
            uint2 st;
            int it = 0;
            do { st = ld_home2(p_str + 1); } while (!__all_sync(0xffffffffu, (st.x ^ old) & 1u) && ++it < SPIN_MAX);
            COUNT(30, it);
            const unsigned tmax = now + (unsigned)min(__reduce_max_sync(0xffffffffu, (int)(st.x - now)), 100000);
            if (lane == 0) sts32(sm + SM_G + 16, tmax + P.d5);
            bar_arrive(4, 288);
            STAMP(23);
            while ((int)(gtimer() - (tmax + P.d6)) < 0) {}
            st = ld_home2(p_str);
            while (!__all_sync(0xffffffffu, (st.x ^ old) & 1u) && ++it < SPIN_MAX) st = ld_home2(p_str);
            const float M = warp_max(__uint_as_float(st.y));
            const float ff = ex2(__uint_as_float(st.y) - M);
            const uint32_t f2 = pack_bf16(ff, ff);
            sts32(sm + SM_F + lane * 4, f2);
            float L = bf_lo(f2) * untagf(st.x);
#pragma unroll
            for (int d = 1; d < 32; d <<= 1) L += shfl_x(L, d);
            if (lane == 0) sts32(sm + SM_G + 8, __float_as_uint(__fdividef(1.f, L)));
            bar_arrive(6, 288);
            STAMP(21);
        }
    }
}

typedef CUresult (*EncodeFn)(CUtensorMap*, CUtensorMapDataType, cuuint32_t, void*, const cuuint64_t*, const cuuint64_t*,
                             const cuuint32_t*, const cuuint32_t*, CUtensorMapInterleave, CUtensorMapSwizzle,
                             CUtensorMapL2promotion, CUtensorMapFloatOOBfill);

void make_map(EncodeFn enc, CUtensorMap* m, const void* base, int rows, int cols, int box_cols, int box_rows, int box_blks) {
    cuuint64_t gd[3] = {64, (cuuint64_t)rows, (cuuint64_t)(cols / 64)};
    cuuint64_t gs[2] = {(cuuint64_t)cols * 2, 128};
    cuuint32_t bd[3] = {(cuuint32_t)box_cols, (cuuint32_t)box_rows, (cuuint32_t)box_blks};
    cuuint32_t es[3] = {1, 1, 1};
    enc(m, CU_TENSOR_MAP_DATA_TYPE_BFLOAT16, 3, const_cast<void*>(base), gd, gs, bd, es, CU_TENSOR_MAP_INTERLEAVE_NONE,
        box_cols == 64 ? CU_TENSOR_MAP_SWIZZLE_128B : box_cols == 32 ? CU_TENSOR_MAP_SWIZZLE_64B : CU_TENSOR_MAP_SWIZZLE_32B,
        CU_TENSOR_MAP_L2_PROMOTION_NONE, CU_TENSOR_MAP_FLOAT_OOB_FILL_NONE);
}

}

extern "C" void kernel_launch(void* const* d_in, const int* in_sizes, int n_in, void* d_out, int out_size) {
    (void)in_sizes; (void)n_in; (void)out_size;
    static EncodeFn enc = nullptr;
    static Scratch* scratch = nullptr;
    if (!enc) {
        void* fn = nullptr;
        cudaDriverEntryPointQueryResult st;
        cudaGetDriverEntryPoint("cuTensorMapEncodeTiled", &fn, cudaEnableDefault, &st);
        enc = (EncodeFn)fn;
        cudaFuncSetAttribute(fused_kernel, cudaFuncAttributeMaxDynamicSharedMemorySize, SMEM_BYTES);
        cudaGetSymbolAddress((void**)&scratch, g_s);
    }
    Params p;
    make_map(enc, &p.m[0], d_in[3], 512, 4096, 64, 64, 1);
    make_map(enc, &p.m[1], d_in[1], 4096, 512, 64, 128, 1);
    make_map(enc, &p.m[2], d_in[7], 640, 1728, 32, 160, 1);
    make_map(enc, &p.m[3], d_in[4], 512, 4096, 64, 64, 1);
    make_map(enc, &p.m[4], d_in[5], 4096, 640, 64, 16, 5);
    make_map(enc, &p.m[5], d_in[8], 1728, 640, 16, 216, 1);
    p.x = (const __nv_bfloat16*)d_in[0];
    p.wq = (const __nv_bfloat16*)d_in[2];
    p.gate = (const __nv_bfloat16*)d_in[9];
    p.out = (__nv_bfloat16*)d_out;
    p.s = scratch;
    static const int gap[NCHUNK] = {1540, 260, 198, 240, 560, 280, 301, 295, 388, 145, 420, 226, 348, 451, 314, 312, 480, 413, 593, 61, 9, 129};
    for (int i = 0, t = 0; i < 32; i++) {
        t += i < NCHUNK ? gap[i] : 0;
        p.due[i] = t;
        p.stag[i] = i < 4 ? 165 : i < NCHUNK - 3 ? 445 : 405;
    }
    p.ta = 4150;
    p.tb = 4500;
    p.d3 = 200;
    p.d5 = 1150;
    p.d6 = 900;
    p.d4 = 600;
    fused_kernel<<<NCTA, NTHREADS, SMEM_BYTES>>>(p);
}
```

```cpp
#include <cuda_runtime.h>
#include <cuda.h>
#include <cuda_bf16.h>
#include <stdint.h>

namespace {

constexpr int NCTA = 128;
constexpr int NTHREADS = 384;
constexpr int SPIN_MAX = 1 << 18;

constexpr int SM_WUK = 0;
constexpr int SM_CKV = SM_WUK + 32768;
constexpr int SM_WUV = SM_CKV + 65536;
constexpr int SM_WO  = SM_WUV + 32768;
constexpr int SM_W1  = SM_WO + 40960;
constexpr int SM_W2  = SM_CKV;
constexpr int SM_SPR = SM_W1 + 20480;
constexpr int SM_QS  = SM_WUK;
constexpr int SM_SPL = SM_WUK + 8192;
constexpr int SM_P   = SM_WUK + 16384;
constexpr int SM_FIN = SM_WUK + 20480;
constexpr int SM_XC  = SM_WUK + 24576;
constexpr int SM_XH  = SM_XC + 2048;
constexpr int SM_XQ  = SM_SPR + 8192;
constexpr int SM_XS  = SM_XQ + 4096;
constexpr int SM_G   = SM_XS + 640;
constexpr int SM_F   = SM_G + 32;
constexpr int SM_BAR = SM_F + 128;
constexpr int SMEM_BYTES = SM_BAR + 32 * 8;
static_assert(SMEM_BYTES <= 232448, "smem");

constexpr int B_WUK = 0, B_CKV = 4, B_W1 = 8, B_WUV = 10, B_WO = 14, B_W2 = 18, B_SP = 19, B_XC = 20, B_XH = 21, B_XQ = 22, B_FB = 23, B_DEAD = 24, NBAR = 25;
constexpr int NCHUNK = 22;

struct Scratch {
    uint4    e3[32 * 2 * 8 * 32 * 4];
    uint4    e4[80 * NCTA * 2];
    uint4    e2[2 * 32 * 64];
    uint2    st[32 * 32 * 4];
    uint4    eh[432];
    unsigned epoch;
};
__device__ __align__(1024) Scratch g_s;

struct Params {
    const __nv_bfloat16* wq;
    const __nv_bfloat16* x;
    Scratch* s;
    const __nv_bfloat16* gate;
    __nv_bfloat16* out;
    int due[32], stag[32];
    int d3, d4, d5, d6, ta, tb;
    alignas(64) CUtensorMap m[6];
};

#define STAMP(i)
#define COUNT(i, it)

__device__ __forceinline__ unsigned clock32() { unsigned c; asm volatile("mov.u32 %0, %%clock;" : "=r"(c) :: "memory"); return c; }
__device__ __forceinline__ unsigned gtimer() { unsigned c; asm volatile("mov.u32 %0, %%globaltimer_lo;" : "=r"(c) :: "memory"); return c; }

__device__ __forceinline__ uint4 ldg_stream(const void* p) {
    uint4 v;
    asm volatile("ld.global.nc.L1::no_allocate.v4.u32 {%0,%1,%2,%3}, [%4];"
                 : "=r"(v.x), "=r"(v.y), "=r"(v.z), "=r"(v.w) : "l"(p));
    return v;
}
__device__ __forceinline__ uint4 ld_poll4(const void* p) {
    uint4 v;
    asm volatile("ld.relaxed.gpu.global.v4.u32 {%0,%1,%2,%3}, [%4];"
                 : "=r"(v.x), "=r"(v.y), "=r"(v.z), "=r"(v.w) : "l"(p) : "memory");
    return v;
}
__device__ __forceinline__ uint4 ld_poll2x64(const void* p) {
    uint4 v;
    asm volatile("{.reg .b64 a, b; ld.relaxed.gpu.global.v2.b64 {a, b}, [%4]; mov.b64 {%0,%1}, a; mov.b64 {%2,%3}, b;}"
                 : "=r"(v.x), "=r"(v.y), "=r"(v.z), "=r"(v.w) : "l"(p) : "memory");
    return v;
}
__device__ __forceinline__ uint2 ld_poll64(const void* p) {
    uint2 v;
    asm volatile("{.reg .b64 a; ld.relaxed.gpu.global.b64 a, [%2]; mov.b64 {%0,%1}, a;}" : "=r"(v.x), "=r"(v.y) : "l"(p) : "memory");
    return v;
}
__device__ __forceinline__ unsigned ld_poll1(const void* p) {
    unsigned v;
    asm volatile("ld.relaxed.gpu.global.u32 %0, [%1];" : "=r"(v) : "l"(p) : "memory");
    return v;
}
__device__ __forceinline__ void st_pub2x64(void* p, unsigned a, unsigned b, unsigned c, unsigned d) {
    asm volatile("{.reg .b64 x, y; mov.b64 x, {%1,%2}; mov.b64 y, {%3,%4}; st.relaxed.gpu.global.v2.b64 [%0], {x, y};}"
                 :: "l"(p), "r"(a), "r"(b), "r"(c), "r"(d) : "memory");
}
__device__ __forceinline__ void st_pub64(void* p, unsigned a, unsigned b) {
    asm volatile("{.reg .b64 x; mov.b64 x, {%1,%2}; st.relaxed.gpu.global.b64 [%0], x;}" :: "l"(p), "r"(a), "r"(b) : "memory");
}
__device__ __forceinline__ void st_pub1(void* p, unsigned a) {
    asm volatile("st.relaxed.gpu.global.u32 [%0], %1;" :: "l"(p), "r"(a) : "memory");
}
__device__ __forceinline__ unsigned tagw(unsigned w, unsigned tag) { return (w & ~1u) | tag; }
__device__ __forceinline__ unsigned tagf(float v, unsigned tag) { return (__float_as_uint(v) & ~1u) | tag; }
__device__ __forceinline__ float untagf(unsigned w) { return __uint_as_float(w & ~1u); }

__device__ __forceinline__ void mbar_wait(uint32_t bar) {
    uint32_t ok;
    int it = 0;
#pragma unroll 1
    do {
        asm volatile("{.reg .pred p; mbarrier.try_wait.parity.shared::cta.b64 p, [%1], 0; selp.u32 %0,1,0,p;}"
                     : "=r"(ok) : "r"(bar) : "memory");
    } while (!ok && ++it < SPIN_MAX);
}
__device__ __forceinline__ void bar_sync(int id, int n) { asm volatile("bar.sync %0, %1;" :: "r"(id), "r"(n) : "memory"); }
__device__ __forceinline__ void bar_arrive(int id, int n) { asm volatile("bar.arrive %0, %1;" :: "r"(id), "r"(n) : "memory"); }
__device__ __forceinline__ uint32_t mapa(uint32_t a, uint32_t rank) {
    uint32_t r;
    asm("mapa.shared::cluster.u32 %0, %1, %2;" : "=r"(r) : "r"(a), "r"(rank));
    return r;
}
__device__ __forceinline__ void st_async4(uint32_t a, float x, float y, float z, float w, uint32_t bar) {
    asm volatile("st.async.weak.shared::cluster.mbarrier::complete_tx::bytes.v4.f32 [%0], {%1,%2,%3,%4}, [%5];"
                 :: "r"(a), "f"(x), "f"(y), "f"(z), "f"(w), "r"(bar) : "memory");
}
__device__ __forceinline__ void st_async2(uint32_t a, uint32_t x, uint32_t y, uint32_t bar) {
    asm volatile("st.async.weak.shared::cluster.mbarrier::complete_tx::bytes.v2.b32 [%0], {%1,%2}, [%3];"
                 :: "r"(a), "r"(x), "r"(y), "r"(bar) : "memory");
}

__device__ __forceinline__ void ldsm4(uint32_t a, uint32_t (&r)[4]) {
    asm volatile("ldmatrix.sync.aligned.m8n8.x4.shared.b16 {%0,%1,%2,%3}, [%4];"
                 : "=r"(r[0]), "=r"(r[1]), "=r"(r[2]), "=r"(r[3]) : "r"(a) : "memory");
}
__device__ __forceinline__ void ldsm4t(uint32_t a, uint32_t (&r)[4]) {
    asm volatile("ldmatrix.sync.aligned.m8n8.x4.trans.shared.b16 {%0,%1,%2,%3}, [%4];"
                 : "=r"(r[0]), "=r"(r[1]), "=r"(r[2]), "=r"(r[3]) : "r"(a) : "memory");
}
__device__ __forceinline__ void mma(float (&c)[4], uint32_t a0, uint32_t a1, uint32_t a2, uint32_t a3, uint32_t b0, uint32_t b1) {
    asm("mma.sync.aligned.m16n8k16.row.col.f32.bf16.bf16.f32 {%0,%1,%2,%3}, {%4,%5,%6,%7}, {%8,%9}, {%0,%1,%2,%3};"
        : "+f"(c[0]), "+f"(c[1]), "+f"(c[2]), "+f"(c[3])
        : "r"(a0), "r"(a1), "r"(a2), "r"(a3), "r"(b0), "r"(b1));
}
__device__ __forceinline__ uint32_t pack_bf16(float lo, float hi) {
    uint32_t r;
    asm("cvt.rn.bf16x2.f32 %0, %1, %2;" : "=r"(r) : "f"(hi), "f"(lo));
    return r;
}
__device__ __forceinline__ float bf_lo(uint32_t w) { return __uint_as_float(w << 16); }
__device__ __forceinline__ float bf_hi(uint32_t w) { return __uint_as_float(w & 0xFFFF0000u); }
__device__ __forceinline__ float ex2(float x) { float y; asm("ex2.approx.ftz.f32 %0, %1;" : "=f"(y) : "f"(x)); return y; }
__device__ __forceinline__ uint4 lds128(uint32_t a) {
    uint4 v;
    asm volatile("ld.shared.v4.u32 {%0,%1,%2,%3}, [%4];" : "=r"(v.x), "=r"(v.y), "=r"(v.z), "=r"(v.w) : "r"(a) : "memory");
    return v;
}
__device__ __forceinline__ float2 lds64f(uint32_t a) {
    float2 v;
    asm volatile("ld.shared.v2.f32 {%0,%1}, [%2];" : "=f"(v.x), "=f"(v.y) : "r"(a) : "memory");
    return v;
}
__device__ __forceinline__ uint32_t lds32(uint32_t a) {
    uint32_t v;
    asm volatile("ld.shared.u32 %0, [%1];" : "=r"(v) : "r"(a) : "memory");
    return v;
}
__device__ __forceinline__ void sts128(uint32_t a, float x, float y, float z, float w) {
    asm volatile("st.shared.v4.f32 [%0], {%1,%2,%3,%4};" :: "r"(a), "f"(x), "f"(y), "f"(z), "f"(w) : "memory");
}
__device__ __forceinline__ void sts64(uint32_t a, uint32_t x, uint32_t y) {
    asm volatile("st.shared.v2.u32 [%0], {%1,%2};" :: "r"(a), "r"(x), "r"(y) : "memory");
}
__device__ __forceinline__ void sts32(uint32_t a, uint32_t x) {
    asm volatile("st.shared.u32 [%0], %1;" :: "r"(a), "r"(x) : "memory");
}
__device__ __forceinline__ void sts16(uint32_t a, uint32_t x) {
    asm volatile("st.shared.u16 [%0], %1;" :: "r"(a), "h"((unsigned short)x) : "memory");
}
__device__ __forceinline__ void fma8(float (&acc)[8], float s, const uint4& v) {
    acc[0] = fmaf(s, bf_lo(v.x), acc[0]); acc[1] = fmaf(s, bf_hi(v.x), acc[1]);
    acc[2] = fmaf(s, bf_lo(v.y), acc[2]); acc[3] = fmaf(s, bf_hi(v.y), acc[3]);
    acc[4] = fmaf(s, bf_lo(v.z), acc[4]); acc[5] = fmaf(s, bf_hi(v.z), acc[5]);
    acc[6] = fmaf(s, bf_lo(v.w), acc[6]); acc[7] = fmaf(s, bf_hi(v.w), acc[7]);
}
__device__ __forceinline__ float warp_max(float v) {
    int k = __float_as_int(v);
    k ^= (k >> 31) & 0x7FFFFFFF;
    asm("redux.sync.max.s32 %0, %0, 0xffffffff;" : "+r"(k));
    k ^= (k >> 31) & 0x7FFFFFFF;
    return __int_as_float(k);
}

__device__ __forceinline__ void st_async1(uint32_t a, float x, uint32_t bar) {
    asm volatile("st.async.weak.shared::cluster.mbarrier::complete_tx::bytes.f32 [%0], %1, [%2];" :: "r"(a), "f"(x), "r"(bar) : "memory");
}
__device__ __forceinline__ void st_pub4(void* p, unsigned a, unsigned b, unsigned c, unsigned d) {
    asm volatile("st.relaxed.gpu.global.v4.u32 [%0], {%1,%2,%3,%4};" :: "l"(p), "r"(a), "r"(b), "r"(c), "r"(d) : "memory");
}
__device__ __forceinline__ uint32_t ldg32(const void* p) {
    uint32_t v;
    asm volatile("ld.global.nc.u32 %0, [%1];" : "=r"(v) : "l"(p));
    return v;
}
__device__ __forceinline__ void mma4(float (&c)[4], const uint32_t (&a)[4], uint32_t b0, uint32_t b1) { mma(c, a[0], a[1], a[2], a[3], b0, b1); }
__device__ __forceinline__ float shfl_x(float v, int m) { return __shfl_xor_sync(0xffffffffu, v, m); }
__device__ __forceinline__ unsigned chk(unsigned acc, unsigned w, unsigned tag) {
    unsigned d;
    asm("lop3.b32 %0, %1, %2, %3, 0xF6;" : "=r"(d) : "r"(acc), "r"(w), "r"(tag));
    return d;
}
__device__ __forceinline__ unsigned chk4(unsigned acc, const uint4& v, unsigned tag) { return chk(chk(chk(chk(acc, v.x, tag), v.y, tag), v.z, tag), v.w, tag); }
__device__ __forceinline__ void sts128u(uint32_t a, uint32_t x, uint32_t y, uint32_t z, uint32_t w) {
    asm volatile("st.shared.v4.u32 [%0], {%1,%2,%3,%4};" :: "r"(a), "r"(x), "r"(y), "r"(z), "r"(w) : "memory");
}
__device__ __forceinline__ uint32_t add_bf16x2(uint32_t a, uint32_t b) {
    uint32_t d;
    asm("add.rn.bf16x2 %0, %1, %2;" : "=r"(d) : "r"(a & ~1u), "r"(b & ~1u));
    return d;
}
__device__ __forceinline__ void spin_until(unsigned t) { while ((int)(clock32() - t) < 0) {} }
__device__ __forceinline__ uint32_t fma_bf16x2(uint32_t a, uint32_t b, uint32_t c) {
    uint32_t d;
    asm("fma.rn.bf16x2 %0, %1, %2, %3;" : "=r"(d) : "r"(a), "r"(b), "r"(c));
    return d;
}
__device__ __forceinline__ uint32_t mul_bf16x2(uint32_t a, uint32_t b) {
    uint32_t d;
    asm("mul.rn.bf16x2 %0, %1, %2;" : "=r"(d) : "r"(a), "r"(b));
    return d;
}
__device__ __forceinline__ bool mbar_test(uint32_t bar) {
    uint32_t ok;
    asm volatile("{.reg .pred p; mbarrier.test_wait.parity.shared::cta.b64 p, [%1], 0; selp.u32 %0,1,0,p;}" : "=r"(ok) : "r"(bar) : "memory");
    return __all_sync(0xffffffffu, ok);
}
__device__ __forceinline__ uint4 ld_home4(const void* p) {
    uint4 v;
    asm volatile("{.reg .b128 d, z; .reg .b64 lo, hi; mov.b64 lo, 0; mov.b128 z, {lo, lo};"
                 " atom.relaxed.gpu.global.cas.b128 d, [%4], z, z; mov.b128 {lo, hi}, d; mov.b64 {%0,%1}, lo; mov.b64 {%2,%3}, hi;}"
                 : "=r"(v.x), "=r"(v.y), "=r"(v.z), "=r"(v.w) : "l"(p) : "memory");
    return v;
}
__device__ __forceinline__ uint2 ld_home2(const void* p) {
    uint2 v;
    asm volatile("{.reg .b64 a; atom.relaxed.gpu.global.or.b64 a, [%2], 0; mov.b64 {%0,%1}, a;}" : "=r"(v.x), "=r"(v.y) : "l"(p) : "memory");
    return v;
}
#define UNLIKELY(c) __builtin_expect(!!(c), 0)
#define PIN(x) asm volatile("" : "+r"(x))
#define PINL(x) asm volatile("" : "+l"(x))

__global__ void __cluster_dims__(2, 1, 1) __launch_bounds__(NTHREADS, 1)
fused_kernel(const __grid_constant__ Params P)
{
    extern __shared__ __align__(1024) unsigned char smem_raw[];
    const int tid = threadIdx.x;
    const int cl = blockIdx.x >> 1;
    const int r = blockIdx.x & 1;
    const uint32_t sm = (uint32_t)__cvta_generic_to_shared(smem_raw);
    uint4 wv[10];
    uint32_t xw[5];
    if (tid < 256) {
        asm volatile("barrier.cluster.arrive.relaxed.aligned;" ::: "memory");
        const int m0 = 320 * r + 10 * (tid >> 3);
        const __nv_bfloat16* wp = P.wq + (size_t)m0 * 4096 + cl * 64 + (tid & 7) * 8;
#pragma unroll
        for (int i = 0; i < 10; i++) wv[i] = ldg_stream(wp + i * 4096);
#pragma unroll
        for (int i = 0; i < 5; i++) xw[i] = ldg32(P.x + m0 + 2 * i);
    }
    unsigned t0 = 0;
    if (tid >= 256) t0 = gtimer();
    if (tid == 256) {
#pragma unroll
        for (int i = 0; i < B_CKV; i++) asm volatile("mbarrier.init.shared::cta.b64 [%0], 1;" :: "r"(sm + SM_BAR + 8 * i) : "memory");
#pragma unroll
        for (int i = 0; i < B_CKV; i++) asm volatile("mbarrier.arrive.expect_tx.shared::cta.b64 _, [%0], 8192;" :: "r"(sm + SM_BAR + 8 * i) : "memory");
        asm volatile("fence.mbarrier_init.release.cluster;" ::: "memory");
    }
    const int pu = cl < 36 ? cl - 4 : cl - 36, pn = cl < 36 ? 8 : 7;
    const int pv = pu >= 2 * pn ? pu - 2 * pn : pu;
    const int lc = cl < 4 ? cl : cl - pv + (pv >= pn ? 2 * (pv - pn) + 1 : 2 * pv);
    const int b = 2 * lc + r;
    const int h = b >> 2;
    const int pp = lc & 1;
    const int warp = tid >> 5, lane = tid & 31;
    const bool ffn = h < 27;
    Scratch* const S = P.s;

    if (warp < 8) {
        asm volatile("setmaxnreg.inc.sync.aligned.u32 224;");
        const int g = lane >> 2, t = lane & 3, l7 = lane & 7;
        const int kq = warp >> 1, nh = warp & 1;
        const uint32_t smp = mapa(sm, r ^ 1);
        const int row1 = 2 * l7 + ((lane >> 3) & 1);
        uint32_t a_wuk = sm + SM_WUK + (32 * warp + row1) * 128 + (((lane >> 4) ^ (row1 & 7)) << 4);
        unsigned* p_e2w = reinterpret_cast<unsigned*>(S->e2) + (((cl & 1) * 32 + (cl >> 1)) * 2 + r) * (4 * 32) + 16 * warp + 8 * (t & 1) + g;
        const uint4* p_e2r = S->e2 + ((16 * pp + (tid >> 4)) * 2 + r) * 32 + (tid & 15);
        uint32_t a_qsw = sm + SM_QS + (tid >> 4) * 512 + (((tid & 15) ^ ((tid >> 4) & 7)) << 4);
        uint32_t a_qsr = sm + SM_QS + (lane & 15) * 512 + (((lane >> 4) ^ l7) << 4);
        uint32_t a_s = sm + SM_CKV + (16 * warp + l7) * 128 + (((lane >> 3) ^ l7) << 4);
        uint32_t o_spw = warp * 1024 + ((lane ^ (nh << 2)) << 4);
        uint32_t a_ct = sm + SM_CKV + kq * 16384 + lane * 128 + (((4 * nh) ^ l7) << 4);
        uint32_t a_sr = sm + g * 1024 + ((warp ^ (g & 1)) << 6) + t * 16;
        uint2* p_stw = S->st + (16 * pp + 8 * r + warp) * 128 + h * 4 + lane;
        uint4* p_e3w = S->e3 + ((((16 * pp + g) * 2 + r) * 8 + warp) * 32 + h) * 4 + t;
        const uint4* p_e3r = S->e3 + ((h * 2 + r) * 8 + warp) * 128 + lane;
        const int krow = l7 + 8 * (lane >> 4), csel = (lane >> 3) & 1;
        uint32_t a_w1 = sm + SM_W1 + (80 * kq + krow) * 64 + (((2 * nh + csel) ^ (l7 >> 1)) << 4);
        uint32_t a_wuv = sm + SM_WUV + (32 * warp + krow) * 128 + ((csel ^ l7) << 4);
        uint32_t a_fin[5];
#pragma unroll
        for (int i = 0; i < 5; i++) {
            const int N = 10 * (warp & 3) + 2 * i + csel;
            a_fin[i] = sm + (warp >> 2) * 10240 + (N >> 3) * 2048 + krow * 128 + (((N & 7) ^ l7) << 4);
            PIN(a_fin[i]);
        }
        uint32_t b_xc = ((t >> 1) == r ? mapa(sm, r) : smp), b_xh = (nh == r ? mapa(sm, r) : smp);
        uint32_t a_xc = b_xc + SM_XC + (8 * r + warp) * 128 + ((t & 1) * 8 + g) * 8;
        uint32_t a_xh = b_xh + SM_XH + ((t & 1) * 8 + g) * 32 + (4 * r + kq) * 4;
        unsigned* p_e4w = reinterpret_cast<unsigned*>(S->e4) + (10 * warp + t) * (4 * 256) + b * 8 + g;
        PIN(a_wuk); PINL(p_e2w); PINL(p_e2r); PIN(a_s); PIN(a_qsw); PIN(a_qsr); PIN(o_spw); PIN(a_ct); PIN(a_sr);
        PINL(p_stw); PINL(p_e3w); PINL(p_e3r); PIN(a_w1); PIN(a_wuv); PIN(a_xc); PIN(a_xh); PINL(p_e4w);

        {
            float acc[8];
#pragma unroll
            for (int e = 0; e < 8; e++) acc[e] = 0.f;
#pragma unroll
            for (int i = 0; i < 10; i++) fma8(acc, (i & 1) ? bf_hi(xw[i >> 1]) : bf_lo(xw[i >> 1]), wv[i]);
            const bool b4 = lane & 16, b3 = lane & 8;
            float k4[4], k2[2];
#pragma unroll
            for (int e = 0; e < 4; e++) k4[e] = (b4 ? acc[4 + e] : acc[e]) + shfl_x(b4 ? acc[e] : acc[4 + e], 16);
#pragma unroll
            for (int e = 0; e < 2; e++) k2[e] = (b3 ? k4[2 + e] : k4[e]) + shfl_x(b3 ? k4[e] : k4[2 + e], 8);
            asm volatile("barrier.cluster.wait.aligned;" ::: "memory");
            const uint32_t o = SM_XQ + (8 * r + warp) * 256 + (4 * l7 + (lane >> 3)) * 8;
            const uint32_t smo = mapa(sm, r);
            st_async2(smp + o, __float_as_uint(k2[0]), __float_as_uint(k2[1]), smp + SM_BAR + 8 * B_XQ);
            st_async2(smo + o, __float_as_uint(k2[0]), __float_as_uint(k2[1]), smo + SM_BAR + 8 * B_XQ);
        }
        bar_sync(1, 288);
        const unsigned tag = lds32(sm + SM_G + 4);
        t0 = lds32(sm + SM_G + 12);
        {
            mbar_wait(sm + SM_BAR + 8 * B_XQ);
            float2 qv[16];
#pragma unroll
            for (int i = 0; i < 16; i++) qv[i] = lds64f(sm + SM_XQ + i * 256 + lane * 8);
#pragma unroll
            for (int i = 0; i < 8; i++) { qv[i].x += qv[i + 8].x; qv[i].y += qv[i + 8].y; }
#pragma unroll
            for (int i = 0; i < 4; i++) { qv[i].x += qv[i + 4].x; qv[i].y += qv[i + 4].y; }
            qv[0].x = (qv[0].x + qv[2].x) + (qv[1].x + qv[3].x);
            qv[0].y = (qv[0].y + qv[2].y) + (qv[1].y + qv[3].y);
            const uint32_t qw = pack_bf16(qv[0].x, qv[0].y);
            uint32_t qb[8];
#pragma unroll
            for (int i = 0; i < 8; i++) qb[i] = __shfl_sync(0xffffffffu, qw, 4 * i + t);
            STAMP(1);
            mbar_wait(sm + SM_BAR + 8 * (B_WUK + kq));
            uint32_t a[8][4];
#pragma unroll
            for (int s = 0; s < 8; s++) ldsm4((a_wuk ^ ((s & 3) << 5)) + (s >> 2) * 2048, a[s]);
            float c[4][4];
#pragma unroll
            for (int i = 0; i < 4; i++) {
                c[i][0] = c[i][1] = c[i][2] = c[i][3] = 0.f;
                mma4(c[i], a[2 * i], qb[4 * (i & 1)], qb[4 * (i & 1) + 1]);
            }
#pragma unroll
            for (int i = 0; i < 4; i++) mma4(c[i], a[2 * i + 1], qb[4 * (i & 1) + 2], qb[4 * (i & 1) + 3]);
            const float sc = 0.08838834764831845f * 1.4426950408889634f;
            const float lo = ((t & 1) ? c[2][0] + c[3][0] : c[0][0] + c[1][0]) * sc;
            const float hi = ((t & 1) ? c[2][2] + c[3][2] : c[0][2] + c[1][2]) * sc;
            const uint32_t lob = (lo != lo) ? 0x7FFEu : (((__float_as_uint(lo) + 0x10000u) >> 16) & 0xFFFEu);
            if (t < 2) st_pub1(p_e2w, (pack_bf16(0.f, hi) & 0xFFFF0000u) | lob | tag);
        }
        STAMP(2);
        {
            bar_sync(3, 256);
            float s[4][4];
#pragma unroll
            for (int i = 0; i < 4; i++) s[i][0] = s[i][1] = s[i][2] = s[i][3] = 0.f;
            uint32_t ct[4][4][4];
            uint32_t bf[2][4][4];
            uint4 v[4];
#define LOAD_BF(q) _Pragma("unroll") for (int i = 0; i < 4; i++) ldsm4((a_s ^ ((i >> 1) << 6)) + (q) * 16384 + (i & 1) * 1024, bf[(q) & 1][i])
#define LOAD_CT()  _Pragma("unroll") for (int i = 0; i < 16; i++) ldsm4t((a_ct ^ ((i >> 2) << 4)) + (i & 3) * 4096, ct[i >> 2][i & 3])
#define STAGE_Q(st2) do { \
                int it = 0; \
                const unsigned tg = lds32(sm + SM_G + 4);     \
                if (UNLIKELY(chk4(chk4(0u, v[2 * (st2)], tg), v[2 * (st2) + 1], tg) & 1u)) { \
                    do { \
                        v[2 * (st2)] = ld_home4(p_e2r + (st2) * 16); \
                        v[2 * (st2) + 1] = ld_home4(p_e2r + (st2) * 16 + 64 * 32); \
                    } while ((chk4(chk4(0u, v[2 * (st2)], tag), v[2 * (st2) + 1], tag) & 1u) && ++it < SPIN_MAX); \
                    it++; \
                } \
                COUNT(26 + st2, it); \
                const uint4 &x = v[2 * (st2)], &y = v[2 * (st2) + 1]; \
                sts128u(a_qsw + (st2) * 256, add_bf16x2(x.x, y.x), add_bf16x2(x.y, y.y), add_bf16x2(x.z, y.z), add_bf16x2(x.w, y.w)); \
            } while (0)
#define LOAD_QA(q) _Pragma("unroll") for (int i = 0; i < 4; i++) ldsm4((a_qsr ^ (i << 5)) + (q) * 128, qa[(q) & 1][i])
#define S_BLOCK(q) do { \
                const uint32_t (&A)[4][4] = qa[(q) & 1]; const uint32_t (&B)[4][4] = bf[(q) & 1]; \
                mma4(s[0], A[0], B[0][0], B[0][1]); mma4(s[1], A[0], B[1][0], B[1][1]); \
                mma4(s[2], A[1], B[0][2], B[0][3]); mma4(s[3], A[1], B[1][2], B[1][3]); \
                mma4(s[0], A[2], B[2][0], B[2][1]); mma4(s[1], A[2], B[3][0], B[3][1]); \
                mma4(s[2], A[3], B[2][2], B[2][3]); mma4(s[3], A[3], B[3][2], B[3][3]); \
            } while (0)
            uint32_t qa[2][4][4];
            while (gtimer() - t0 < P.ta) {}
            v[0] = ld_poll4(p_e2r);
            v[1] = ld_poll4(p_e2r + 64 * 32);
            mbar_wait(sm + SM_BAR + 8 * (B_CKV + 0));
            LOAD_BF(0);
            STAGE_Q(0);
            while (gtimer() - t0 < P.tb) {}
            v[2] = ld_poll4(p_e2r + 16);
            v[3] = ld_poll4(p_e2r + 16 + 64 * 32);
            mbar_wait(sm + SM_BAR + 8 * (B_CKV + 1));
            LOAD_BF(1);
            bar_sync(3, 256);
            LOAD_QA(0);
            LOAD_QA(1);
            S_BLOCK(0);
            S_BLOCK(1);
            if (kq < 2) { LOAD_CT(); }
            mbar_wait(sm + SM_BAR + 8 * (B_CKV + 2));
            LOAD_BF(2);
            mbar_wait(sm + SM_BAR + 8 * (B_CKV + 3));
            LOAD_BF(3);
            STAGE_Q(1);
            bar_sync(3, 256);
            LOAD_QA(2);
            LOAD_QA(3);
            STAMP(4);
            S_BLOCK(2);
            S_BLOCK(3);
            {
                const float u0 = s[0][0] + s[2][0], u1 = s[0][1] + s[2][1], u2 = s[1][0] + s[3][0], u3 = s[1][1] + s[3][1];
                const float v0 = s[0][2] + s[2][2], v1 = s[0][3] + s[2][3], v2 = s[1][2] + s[3][2], v3 = s[1][3] + s[3][3];
                st_async4(smp + SM_SPR + o_spw, u0, u1, u2, u3, smp + SM_BAR + 8 * B_SP);
                st_async4(smp + SM_SPR + 512 + o_spw, v0, v1, v2, v3, smp + SM_BAR + 8 * B_SP);
                sts128(sm + SM_SPL + o_spw, u0, u1, u2, u3);
                sts128(sm + SM_SPL + 512 + o_spw, v0, v1, v2, v3);
            }
            if (kq >= 2) { LOAD_CT(); }
            bar_sync(2, 288);
            {
                const uint4 ul = lds128(a_sr + SM_SPL), vl = lds128(a_sr + SM_SPL + 512);
                mbar_wait(sm + SM_BAR + 8 * B_SP);
                STAMP(6);
                const uint4 ur = lds128(a_sr + SM_SPR), vr = lds128(a_sr + SM_SPR + 512);
                const float u0 = __uint_as_float(ul.x) + __uint_as_float(ur.x), u1 = __uint_as_float(ul.y) + __uint_as_float(ur.y);
                const float u2 = __uint_as_float(ul.z) + __uint_as_float(ur.z), u3 = __uint_as_float(ul.w) + __uint_as_float(ur.w);
                const float v0 = __uint_as_float(vl.x) + __uint_as_float(vr.x), v1 = __uint_as_float(vl.y) + __uint_as_float(vr.y);
                const float v2 = __uint_as_float(vl.z) + __uint_as_float(vr.z), v3 = __uint_as_float(vl.w) + __uint_as_float(vr.w);
                const float mu = warp_max(fmaxf(fmaxf(u0, u1), fmaxf(u2, u3)));
                const float mv = warp_max(fmaxf(fmaxf(v0, v1), fmaxf(v2, v3)));
                const uint32_t a0 = pack_bf16(ex2(u0 - mu), ex2(u1 - mu)), a2 = pack_bf16(ex2(u2 - mu), ex2(u3 - mu));
                const uint32_t a1 = pack_bf16(ex2(v0 - mv), ex2(v1 - mv)), a3 = pack_bf16(ex2(v2 - mv), ex2(v3 - mv));
                sts128u(sm + SM_P + g * 512 + warp * 64 + t * 16, a0, a1, a2, a3);
                bar_sync(3, 256);
                uint4 pa[8];
#pragma unroll
                for (int q = 0; q < 8; q++) pa[q] = lds128(sm + SM_P + q * 512 + lane * 16);
                float o[2][4][4];
#pragma unroll
                for (int n = 0; n < 4; n++)
#pragma unroll
                    for (int e = 0; e < 4; e++) o[0][n][e] = o[1][n][e] = 0.f;
#pragma unroll
                for (int i = 0; i < 4; i++) {
#pragma unroll
                    for (int n = 0; n < 4; n++) mma(o[0][n], pa[2 * i].x, pa[2 * i].y, pa[2 * i].z, pa[2 * i].w, ct[n][i][0], ct[n][i][1]);
#pragma unroll
                    for (int n = 0; n < 4; n++) mma(o[1][n], pa[2 * i + 1].x, pa[2 * i + 1].y, pa[2 * i + 1].z, pa[2 * i + 1].w, ct[n][i][2], ct[n][i][3]);
                }
                const uint32_t q0 = r ? a1 : a0, q1 = r ? a3 : a2;
                float l = (bf_lo(q0) + bf_hi(q0)) + (bf_lo(q1) + bf_hi(q1));
#pragma unroll
                for (int d = 1; d < 32; d <<= 1) l += shfl_x(l, d);
                if (lane == 0) st_pub64(p_stw, tagf(l, tag), __float_as_uint(r ? mv : mu));
                uint32_t w0[4], w1[4];
#pragma unroll
                for (int n = 0; n < 4; n++) {
                    w0[n] = pack_bf16(o[0][n][0] + o[1][n][0], o[0][n][1] + o[1][n][1]);
                    w1[n] = pack_bf16(o[0][n][2] + o[1][n][2], o[0][n][3] + o[1][n][3]);
                }
                st_pub2x64(p_e3w, tagw(w0[0], tag), w0[1], tagw(w0[2], tag), w0[3]);
                st_pub2x64(p_e3w + 8 * 2 * 8 * 32 * 4, tagw(w1[0], tag), w1[1], tagw(w1[2], tag), w1[3]);
            }
        }
        STAMP(8);
        if (ffn) {
            const uint32_t xa = sm + SM_XS + 160 * kq + 4 * t;
            uint32_t xb[5][2];
#pragma unroll
            for (int s = 0; s < 5; s++) { xb[s][0] = lds32(xa + s * 32); xb[s][1] = lds32(xa + s * 32 + 16); }
            mbar_wait(sm + SM_BAR + 8 * (B_W1 + (warp >> 2)));
            uint32_t aw[5][4];
#pragma unroll
            for (int s = 0; s < 5; s++) ldsm4t(a_w1 + s * 1024, aw[s]);
            float c0[4] = {0.f, 0.f, 0.f, 0.f}, c1[4] = {0.f, 0.f, 0.f, 0.f};
#pragma unroll
            for (int s = 0; s < 5; s++) mma4((s & 1) ? c1 : c0, aw[s], xb[s][0], xb[s][1]);
            if (t < 2) st_async1(a_xh, t ? c0[2] + c1[2] : c0[0] + c1[0], b_xh + SM_BAR + 8 * B_XH);
        }
        float invl;
        {
            uint32_t a[8][4];
            uint4 v[4];
            uint32_t fw[4];
            int it = 0;
            bar_sync(4, 288);
            {
                const unsigned tq = lds32(sm + SM_G + 16);
                while ((int)(gtimer() - tq) < 0) {}
            }
#pragma unroll
            for (int i = 0; i < 4; i++) v[i] = ld_poll2x64(p_e3r + i * 32);
            STAMP(24);
            if (ffn && warp == 0) {
                mbar_wait(sm + SM_BAR + 8 * B_XH);
                const uint4 u = lds128(sm + SM_XH + (lane & 15) * 32), y = lds128(sm + SM_XH + (lane & 15) * 32 + 16);
                float hv = ((__uint_as_float(u.x) + __uint_as_float(u.y)) + (__uint_as_float(u.z) + __uint_as_float(u.w))) +
                           ((__uint_as_float(y.x) + __uint_as_float(y.y)) + (__uint_as_float(y.z) + __uint_as_float(y.w)));
                hv = bf_lo(pack_bf16(hv, 0.f));
                hv = __fdividef(hv, 1.f + __expf(-hv)) * (1.f - __uint_as_float(lds32(sm + SM_G)));
                if (lane < 16) st_pub1(reinterpret_cast<unsigned*>(S->eh) + 16 * b + 2 * (lane & 6) + 2 * (lane >> 3) + (lane & 1), tagf(hv, tag));
            }
            mbar_wait(sm + SM_BAR + 8 * (B_WUV + kq));
#pragma unroll
            for (int i = 0; i < 8; i++) ldsm4t((a_wuv ^ ((i >> 1) << 5)) + (i & 1) * 2048, a[i]);
            bar_sync(6, 288);
#pragma unroll
            for (int i = 0; i < 4; i++) fw[i] = lds32(sm + SM_F + (8 * i + g) * 4);
            invl = __uint_as_float(lds32(sm + SM_G + 8));
            {
                const unsigned tg = lds32(sm + SM_G + 4);
                unsigned bad = 0u;
#pragma unroll
                for (int i = 0; i < 4; i++) bad = chk(chk(bad, v[i].x, tg), v[i].z, tg);
                if (UNLIKELY(bad & 1u)) {
                    do {
                        bad = 0u;
#pragma unroll
                        for (int i = 0; i < 4; i++) v[i] = ld_home4(p_e3r + i * 32);
#pragma unroll
                        for (int i = 0; i < 4; i++) bad = chk(chk(bad, v[i].x, tag), v[i].z, tag);
                    } while ((bad & 1u) && ++it < SPIN_MAX);
                    it++;
                }
            }
            COUNT(28, it);
            __syncwarp();
            STAMP(10);
            uint32_t bx = mul_bf16x2(fw[0], v[0].x & ~1u), by = mul_bf16x2(fw[0], v[0].y), bz = mul_bf16x2(fw[0], v[0].z & ~1u), bw = mul_bf16x2(fw[0], v[0].w);
#pragma unroll
            for (int i = 1; i < 4; i++) {
                bx = fma_bf16x2(fw[i], v[i].x & ~1u, bx); by = fma_bf16x2(fw[i], v[i].y, by);
                bz = fma_bf16x2(fw[i], v[i].z & ~1u, bz); bw = fma_bf16x2(fw[i], v[i].w, bw);
            }
            float c[4][4];
#pragma unroll
            for (int i = 0; i < 4; i++) {
                c[i][0] = c[i][1] = c[i][2] = c[i][3] = 0.f;
                mma4(c[i], a[2 * i], bx, by);
            }
#pragma unroll
            for (int i = 0; i < 4; i++) mma4(c[i], a[2 * i + 1], bz, bw);
            float e[8], k4[4];
#pragma unroll
            for (int i = 0; i < 4; i++) { e[2 * i] = c[i][0] + c[i][1]; e[2 * i + 1] = c[i][2] + c[i][3]; }
            const bool t1 = t & 2, t0 = t & 1;
#pragma unroll
            for (int i = 0; i < 4; i++) k4[i] = (t1 ? e[4 + i] : e[i]) + shfl_x(t1 ? e[i] : e[4 + i], 2);
            const float k0 = (t0 ? k4[2] : k4[0]) + shfl_x(t0 ? k4[0] : k4[2], 1);
            const float k1 = (t0 ? k4[3] : k4[1]) + shfl_x(t0 ? k4[1] : k4[3], 1);
            st_async2(a_xc, __float_as_uint(k0), __float_as_uint(k1), b_xc + SM_BAR + 8 * B_XC);
        }
        const bool red = b < 80;
        const uint4* p_eh = S->eh + (27 * r + min(warp + 4 * g, 26)) * 8 + t;
        uint4 hv0, hv1;
        if (red && warp < 4) { hv0 = ld_poll4(p_eh); hv1 = ld_poll4(p_eh + 4); }
        {
            float c[5][4];
#pragma unroll
            for (int i = 0; i < 5; i++) c[i][0] = c[i][1] = c[i][2] = c[i][3] = 0.f;
            const int half = warp >> 2;
            const float gt = __uint_as_float(lds32(sm + SM_G));
            uint32_t wa[2][5][4];
            mbar_wait(sm + SM_BAR + 8 * (B_WO + half));
#pragma unroll
            for (int i = 0; i < 5; i++) ldsm4t(a_fin[i] + SM_WO, wa[0][i]);
            const bool early = mbar_test(sm + SM_BAR + 8 * (B_WO + 2 + half));
            if (early) {
#pragma unroll
                for (int i = 0; i < 5; i++) ldsm4t(a_fin[i] + SM_WO + 20480, wa[1][i]);
            }
            mbar_wait(sm + SM_BAR + 8 * B_XC);
            STAMP(13);
            float xv[16];
#pragma unroll
            for (int i = 0; i < 16; i++) xv[i] = __uint_as_float(lds32(sm + SM_XC + i * 128 + lane * 4));
#pragma unroll
            for (int i = 0; i < 8; i++) xv[i] += xv[i + 8];
            const float cv = (((xv[0] + xv[4]) + (xv[1] + xv[5])) + ((xv[2] + xv[6]) + (xv[3] + xv[7]))) * (gt * invl);
            const uint32_t w = pack_bf16(cv, shfl_x(cv, 2));
            uint32_t bb[4];
#pragma unroll
            for (int q = 0; q < 4; q++) bb[q] = __shfl_sync(0xffffffffu, w, (q >> 1) * 16 + 4 * t + (q & 1));
#pragma unroll
            for (int i = 0; i < 5; i++) mma4(c[i], wa[0][i], bb[0], bb[1]);
            if (!early) {
                mbar_wait(sm + SM_BAR + 8 * (B_WO + 2 + half));
#pragma unroll
                for (int i = 0; i < 5; i++) ldsm4t(a_fin[i] + SM_WO + 20480, wa[1][i]);
            }
#pragma unroll
            for (int i = 0; i < 5; i++) mma4(c[i], wa[1][i], bb[2], bb[3]);
            const bool t0 = t & 1, t1 = t & 2;
            const float v0 = t1 ? (t0 ? c[1][2] : c[1][0]) : (t0 ? c[0][2] : c[0][0]);
            const float v1 = t1 ? (t0 ? c[3][2] : c[3][0]) : (t0 ? c[2][2] : c[2][0]);
            const float v2 = t0 ? c[4][2] : c[4][0];
            st_pub1(p_e4w, tagf(v0, tag));
            st_pub1(p_e4w + 4 * 4 * 256, tagf(v1, tag));
            if (!t1) st_pub1(p_e4w + 8 * 4 * 256, tagf(v2, tag));
        }
        STAMP(15);
        if (red) {
            if (warp < 4) {
                int it = 0;
                if (UNLIKELY((chk4(0u, hv0, tag) | chk4(0u, hv1, tag)) & 1u)) {
                    do { hv0 = ld_home4(p_eh); hv1 = ld_home4(p_eh + 4); } while (((chk4(0u, hv0, tag) | chk4(0u, hv1, tag)) & 1u) && ++it < SPIN_MAX);
                }
                __syncwarp();
                const bool ok = warp + 4 * g < 27;
                const uint32_t w0 = ok ? pack_bf16(untagf(hv0.x), untagf(hv0.y)) : 0u, w1 = ok ? pack_bf16(untagf(hv0.z), untagf(hv0.w)) : 0u;
                const uint32_t w2 = ok ? pack_bf16(untagf(hv1.x), untagf(hv1.y)) : 0u, w3 = ok ? pack_bf16(untagf(hv1.z), untagf(hv1.w)) : 0u;
                uint32_t hb[14][2];
#pragma unroll
                for (int i = 0; i < 7; i++) {
                    hb[2 * i][0] = __shfl_sync(0xffffffffu, w0, 4 * i + t); hb[2 * i][1] = __shfl_sync(0xffffffffu, w1, 4 * i + t);
                    hb[2 * i + 1][0] = __shfl_sync(0xffffffffu, w2, 4 * i + t); hb[2 * i + 1][1] = __shfl_sync(0xffffffffu, w3, 4 * i + t);
                }
                const uint32_t a_w2 = sm + SM_W2 + (32 * warp + krow) * 32 + ((csel ^ (l7 >> 2)) << 4);
                const uint32_t a_w2l = a_w2 + (warp < 3 ? 6 * 4096 : 0);
                const uint32_t b_fb = ((t & 1) == r ? mapa(sm, r) : smp);
                mbar_wait(sm + SM_BAR + 8 * B_W2);
                uint32_t a[14][4];
#pragma unroll
                for (int i = 0; i < 12; i++) ldsm4t(a_w2 + (i >> 1) * 4096 + (i & 1) * 512, a[i]);
                ldsm4t(a_w2l, a[12]);
                ldsm4t(a_w2l + 512, a[13]);
                float c[4][4];
#pragma unroll
                for (int i = 0; i < 4; i++) c[i][0] = c[i][1] = c[i][2] = c[i][3] = 0.f;
#pragma unroll
                for (int i = 0; i < 14; i++) mma4(c[i & 3], a[i], hb[i][0], hb[i][1]);
                const float e = (t & 1) ? (c[0][2] + c[1][2]) + (c[2][2] + c[3][2]) : (c[0][0] + c[1][0]) + (c[2][0] + c[3][0]);
                if (t < 2) st_async1(b_fb + SM_FIN + g * 48 + 16 + (4 * r + warp) * 4, e, b_fb + SM_BAR + 8 * B_FB);
                STAMP(16);
            } else {
                const uint4* p = S->e4 + b * 256 + (tid - 128);
                spin_until(clock32() + P.d4);
                uint4 u, v;
                int it = 0;
                do { u = ld_poll4(p); v = ld_poll4(p + 128); } while (((chk4(0u, u, tag) | chk4(0u, v, tag)) & 1u) && ++it < SPIN_MAX);
                COUNT(29, it);
                __syncwarp();
                STAMP(17);
                const float s0 = untagf(u.x) + untagf(v.x), s1 = untagf(u.y) + untagf(v.y), s2 = untagf(u.z) + untagf(v.z), s3 = untagf(u.w) + untagf(v.w);
                const bool b4 = lane & 16, b3 = lane & 8;
                const float k0 = (b4 ? s2 : s0) + shfl_x(b4 ? s0 : s2, 16);
                const float k1 = (b4 ? s3 : s1) + shfl_x(b4 ? s1 : s3, 16);
                float s = (b3 ? k1 : k0) + shfl_x(b3 ? k0 : k1, 8);
                s += shfl_x(s, 4);
                s += shfl_x(s, 2);
                if (!(lane & 6)) sts32(sm + SM_FIN + ((lane & 1) * 4 + (lane >> 3)) * 48 + (warp - 4) * 4, __float_as_uint(s));
                bar_sync(7, 128);
                if (warp == 4 && lane < 8) {
                    mbar_wait(sm + SM_BAR + 8 * B_FB);
                    float o[3];
#pragma unroll
                    for (int i = 0; i < 3; i++) {
                        const uint4 u = lds128(sm + SM_FIN + lane * 48 + i * 16);
                        o[i] = (__uint_as_float(u.x) + __uint_as_float(u.y)) + (__uint_as_float(u.z) + __uint_as_float(u.w));
                    }
                    P.out[b * 8 + lane] = __float2bfloat16((o[1] + o[2]) + o[0]);
                    if (b == 0 && lane == 0) st_pub1(&S->epoch, tag);
                }
            }
        }
    } else {
    asm volatile("setmaxnreg.dec.sync.aligned.u32 56;");
    if (warp == 8) {
        __syncwarp();
        asm volatile("barrier.cluster.arrive.relaxed.aligned;" ::: "memory");
        if (lane < 6) asm volatile("prefetch.tensormap [%0];" :: "l"(&P.m[lane]) : "memory");
        const int k = lane;
        const uint32_t bar = sm + SM_BAR + 8 * min(k, B_W2);
        int map, c0 = 0, c1, c2;
        uint32_t dst, due;
        bool pending = true;
        if (k < B_CKV)      { map = 0; c1 = 256 * r + 64 * k;                c2 = cl;                dst = SM_WUK + k * 8192; }
        else if (k < B_W1)  { map = 1; c1 = 128 * h;                         c2 = 4 * r + k - B_CKV; dst = SM_CKV + (k - B_CKV) * 16384; }
        else if (k < B_WUV) { map = 2; c1 = 320 * r + 160 * (k - B_W1);      c2 = h; c0 = 32 * pp;   dst = SM_W1 + (k - B_W1) * 10240; pending = ffn; }
        else if (k < B_WO)  { map = 3; c1 = 256 * r + 64 * (k - B_WUV);      c2 = lc;                dst = SM_WUV + (k - B_WUV) * 8192; }
        else if (k < B_W2)  { map = 4; c1 = 32 * b + 16 * ((k - B_WO) >> 1); c2 = 5 * (k & 1);       dst = SM_WO + (k - B_WO) * 10240; }
        else                { map = 5; c1 = 864 * r + 216 * (k - B_W2);      c2 = lc >> 2; c0 = 16 * (lc & 3); dst = SM_W2 + (k - B_W2) * 6912; pending = b < 80 && k < NCHUNK; }
        const bool mine = pending;
        due = P.due[k] + ((b * 37) & 127) * P.stag[k] / 128;
        int lim = B_CKV;
        while (__any_sync(0xffffffffu, pending)) {
            if (!__any_sync(0xffffffffu, pending && k < lim)) {
                if (lim == B_CKV) { bar_sync(5, 64); lim = B_W2; }
                else { mbar_wait(sm + SM_BAR + 8 * B_DEAD); lim = NCHUNK; }
            }
            if (pending && k < lim && gtimer() - t0 >= due) {
                asm volatile("cp.async.bulk.tensor.3d.shared::cluster.global.mbarrier::complete_tx::bytes [%0], [%1, {%3,%4,%5}], [%2];"
                             :: "r"(sm + dst), "l"(&P.m[map]), "r"(bar), "r"(c0), "r"(c1), "r"(c2) : "memory");
                pending = false;
            }
        }
        if (mine && k >= B_WO) mbar_wait(bar);
        __syncwarp();
        STAMP(22);
    } else if (warp == 9) {
        const unsigned old = ld_poll1(&S->epoch) & 1u;
        uint32_t xv[10], gw[10];
#pragma unroll
        for (int i = 0; i < 10; i++) {
            xv[i] = ldg32(P.x + (i * 32 + lane) * 2);
            gw[i] = ldg32(P.gate + (i * 32 + lane) * 2);
        }
        if (lane == 0) {
#pragma unroll
            for (int i = B_CKV; i < NBAR; i++) asm volatile("mbarrier.init.shared::cta.b64 [%0], 1;" :: "r"(sm + SM_BAR + 8 * i) : "memory");
#pragma unroll
            for (int i = B_CKV; i < B_DEAD; i++) {
                const uint32_t tx = i < B_W1 ? 16384 : i < B_WUV ? 10240 : i < B_WO ? 8192 : i < B_W2 ? 10240 : i == B_W2 ? 27648 :
                                    i == B_SP ? 8192 : i == B_XC ? 2048 : i == B_XQ ? 4096 : i == B_FB ? 256 : 512;
                asm volatile("mbarrier.arrive.expect_tx.shared::cta.b64 _, [%0], %1;" :: "r"(sm + SM_BAR + 8 * i), "r"(tx) : "memory");
            }
            asm volatile("fence.mbarrier_init.release.cluster;" ::: "memory");
        }
        __syncwarp();
        asm volatile("barrier.cluster.arrive.relaxed.aligned;" ::: "memory");
        bar_arrive(5, 64);
        st_pub4(S->e2 + (((cl & 1) * 32 + (cl >> 1)) * 2 + r) * 32 + lane, old, old, old, old);
        st_pub64(S->st + (16 * pp + 8 * r + (lane >> 2)) * 128 + h * 4 + (lane & 3), old, 0u);
        if (lane == 0) { sts32(sm + SM_G + 4, old ^ 1u); sts32(sm + SM_G + 12, t0); }
#pragma unroll
        for (int i = 0; i < 5; i++) st_pub4(&S->e4[(i * 16 + (lane >> 1)) * 256 + b * 2 + (lane & 1)], old, old, old, old);
        float z = 0.f;
#pragma unroll
        for (int i = 0; i < 10; i++) {
            if ((i >= 5) == (r != 0)) sts32(sm + SM_XS + ((i % 5) * 32 + lane) * 4, xv[i]);
            z = fmaf(bf_lo(xv[i]), bf_lo(gw[i]), z);
            z = fmaf(bf_hi(xv[i]), bf_hi(gw[i]), z);
        }
#pragma unroll
        for (int d = 1; d < 32; d <<= 1) z += shfl_x(z, d);
        if (lane == 0) sts32(sm + SM_G, __float_as_uint(__fdividef(1.f, 1.f + __expf(-z))));
        bar_arrive(1, 288);
        {
            bar_sync(2, 288);
            if (lane == 0) asm volatile("mbarrier.arrive.shared::cta.b64 _, [%0];" :: "r"(sm + SM_BAR + 8 * B_DEAD) : "memory");
            mbar_wait(sm + SM_BAR + 8 * B_SP);
            const unsigned now = gtimer();
            if (lane < 8) st_pub64(S->st + (16 * pp + 8 * r + lane) * 128 + h * 4 + 1, (now & ~1u) | (old ^ 1u), 0u);
            const uint2* p_str = S->st + h * 128 + lane * 4;
            while (gtimer() - now < P.d3) {}
            uint2 st;
            int it = 0;
            do { st = ld_home2(p_str + 1); } while (!__all_sync(0xffffffffu, (st.x ^ old) & 1u) && ++it < SPIN_MAX);
            COUNT(30, it);
            const unsigned tmax = now + (unsigned)min(__reduce_max_sync(0xffffffffu, (int)(st.x - now)), 100000);
            if (lane == 0) sts32(sm + SM_G + 16, tmax + P.d5);
            bar_arrive(4, 288);
            STAMP(23);
            while ((int)(gtimer() - (tmax + P.d6)) < 0) {}
            st = ld_home2(p_str);
            while (!__all_sync(0xffffffffu, (st.x ^ old) & 1u) && ++it < SPIN_MAX) st = ld_home2(p_str);
            const float M = warp_max(__uint_as_float(st.y));
            const float ff = ex2(__uint_as_float(st.y) - M);
            const uint32_t f2 = pack_bf16(ff, ff);
            sts32(sm + SM_F + lane * 4, f2);
            float L = bf_lo(f2) * untagf(st.x);
#pragma unroll
            for (int d = 1; d < 32; d <<= 1) L += shfl_x(L, d);
            if (lane == 0) sts32(sm + SM_G + 8, __float_as_uint(__fdividef(1.f, L)));
            bar_arrive(6, 288);
            STAMP(21);
        }
    }
    }
}

typedef CUresult (*EncodeFn)(CUtensorMap*, CUtensorMapDataType, cuuint32_t, void*, const cuuint64_t*, const cuuint64_t*,
                             const cuuint32_t*, const cuuint32_t*, CUtensorMapInterleave, CUtensorMapSwizzle,
                             CUtensorMapL2promotion, CUtensorMapFloatOOBfill);

void make_map(EncodeFn enc, CUtensorMap* m, const void* base, int rows, int cols, int box_cols, int box_rows, int box_blks) {
    cuuint64_t gd[3] = {64, (cuuint64_t)rows, (cuuint64_t)(cols / 64)};
    cuuint64_t gs[2] = {(cuuint64_t)cols * 2, 128};
    cuuint32_t bd[3] = {(cuuint32_t)box_cols, (cuuint32_t)box_rows, (cuuint32_t)box_blks};
    cuuint32_t es[3] = {1, 1, 1};
    enc(m, CU_TENSOR_MAP_DATA_TYPE_BFLOAT16, 3, const_cast<void*>(base), gd, gs, bd, es, CU_TENSOR_MAP_INTERLEAVE_NONE,
        box_cols == 64 ? CU_TENSOR_MAP_SWIZZLE_128B : box_cols == 32 ? CU_TENSOR_MAP_SWIZZLE_64B : CU_TENSOR_MAP_SWIZZLE_32B,
        CU_TENSOR_MAP_L2_PROMOTION_NONE, CU_TENSOR_MAP_FLOAT_OOB_FILL_NONE);
}

}

extern "C" void kernel_launch(void* const* d_in, const int* in_sizes, int n_in, void* d_out, int out_size) {
    (void)in_sizes; (void)n_in; (void)out_size;
    static EncodeFn enc = nullptr;
    static Scratch* scratch = nullptr;
    if (!enc) {
        void* fn = nullptr;
        cudaDriverEntryPointQueryResult st;
        cudaGetDriverEntryPoint("cuTensorMapEncodeTiled", &fn, cudaEnableDefault, &st);
        enc = (EncodeFn)fn;
        cudaFuncSetAttribute(fused_kernel, cudaFuncAttributeMaxDynamicSharedMemorySize, SMEM_BYTES);
        cudaGetSymbolAddress((void**)&scratch, g_s);
    }
    Params p;
    make_map(enc, &p.m[0], d_in[3], 512, 4096, 64, 64, 1);
    make_map(enc, &p.m[1], d_in[1], 4096, 512, 64, 128, 1);
    make_map(enc, &p.m[2], d_in[7], 640, 1728, 32, 160, 1);
    make_map(enc, &p.m[3], d_in[4], 512, 4096, 64, 64, 1);
    make_map(enc, &p.m[4], d_in[5], 4096, 640, 64, 16, 5);
    make_map(enc, &p.m[5], d_in[8], 1728, 640, 16, 216, 1);
    p.x = (const __nv_bfloat16*)d_in[0];
    p.wq = (const __nv_bfloat16*)d_in[2];
    p.gate = (const __nv_bfloat16*)d_in[9];
    p.out = (__nv_bfloat16*)d_out;
    p.s = scratch;
    static const int gap[NCHUNK] = {1540, 260, 198, 240, 560, 280, 301, 295, 388, 145, 420, 226, 348, 451, 314, 252, 540, 428, 608, 76, 9, 144};
    for (int i = 0, t = 0; i < 32; i++) {
        t += i < NCHUNK ? gap[i] : 0;
        p.due[i] = t;
        p.stag[i] = i < 4 ? 165 : i < NCHUNK - 3 ? 445 : 405;
    }
    p.ta = 4150;
    p.tb = 4500;
    p.d3 = 200;
    p.d5 = 1150;
    p.d6 = 850;
    p.d4 = 600;
    fused_kernel<<<NCTA, NTHREADS, SMEM_BYTES>>>(p);
}
```

```cpp
#include <cuda_runtime.h>
#include <cuda.h>
#include <cuda_bf16.h>
#include <stdint.h>

namespace {

constexpr int NCTA = 128;
constexpr int NTHREADS = 384;
constexpr int SPIN_MAX = 1 << 18;

constexpr int SM_WUK = 0;
constexpr int SM_CKV = SM_WUK + 32768;
constexpr int SM_WUV = SM_CKV + 65536;
constexpr int SM_WO  = SM_WUV + 32768;
constexpr int SM_WQ  = SM_WO;
constexpr int SM_W1  = SM_WO + 40960;
constexpr int SM_W2  = SM_CKV;
constexpr int SM_SPR = SM_W1 + 20480;
constexpr int SM_QS  = SM_WUK;
constexpr int SM_SPL = SM_WUK + 8192;
constexpr int SM_P   = SM_WUK + 16384;
constexpr int SM_FIN = SM_WUK + 20480;
constexpr int SM_XC  = SM_WUK + 24576;
constexpr int SM_XH  = SM_XC + 2048;
constexpr int SM_XQ  = SM_SPR + 8192;
constexpr int SM_XS  = SM_XQ + 4096;
constexpr int SM_G   = SM_XS + 640;
constexpr int SM_F   = SM_G + 32;
constexpr int SM_BAR = SM_F + 128;
constexpr int SMEM_BYTES = SM_BAR + 32 * 8;
static_assert(SMEM_BYTES <= 232448, "smem");

constexpr int B_WUK = 0, B_CKV = 4, B_W1 = 8, B_WUV = 10, B_WO = 14, B_W2 = 18;
constexpr int B_SP = 19, B_XC = 20, B_XH = 21, B_XQ = 22, B_FB = 23, B_DEAD = 24, NBAR = 25, B_WQ = 25;
constexpr int NCHUNK = 22;

struct Scratch {
    uint4    e3[32 * 2 * 8 * 32 * 4];
    uint4    e4[80 * NCTA * 2];
    uint4    e2[2 * 32 * 64];
    uint2    st[32 * 32 * 4];
    uint4    eh[432];
    unsigned epoch;
};
__device__ __align__(1024) Scratch g_s;

struct Params {
    const __nv_bfloat16* wq;
    const __nv_bfloat16* x;
    Scratch* s;
    const __nv_bfloat16* gate;
    __nv_bfloat16* out;
    int2 sched[32];
    int d3, d4, d5, d6, ta, tb, da, db, dc;
    alignas(64) CUtensorMap m[7];
};

__device__ __forceinline__ unsigned gtimer() { unsigned c; asm volatile("mov.u32 %0, %%globaltimer_lo;" : "=r"(c) :: "memory"); return c; }

__device__ __forceinline__ uint4 ld_poll4(const void* p) {
    uint4 v;
    asm volatile("ld.relaxed.gpu.global.v4.u32 {%0,%1,%2,%3}, [%4];"
                 : "=r"(v.x), "=r"(v.y), "=r"(v.z), "=r"(v.w) : "l"(p) : "memory");
    return v;
}
__device__ __forceinline__ uint4 ld_poll2x64(const void* p) {
    uint4 v;
    asm volatile("{.reg .b64 a, b; ld.relaxed.gpu.global.v2.b64 {a, b}, [%4]; mov.b64 {%0,%1}, a; mov.b64 {%2,%3}, b;}"
                 : "=r"(v.x), "=r"(v.y), "=r"(v.z), "=r"(v.w) : "l"(p) : "memory");
    return v;
}
__device__ __forceinline__ unsigned ld_poll1(const void* p) {
    unsigned v;
    asm volatile("ld.relaxed.gpu.global.u32 %0, [%1];" : "=r"(v) : "l"(p) : "memory");
    return v;
}
__device__ __forceinline__ void st_pub2x64(void* p, unsigned a, unsigned b, unsigned c, unsigned d) {
    asm volatile("{.reg .b64 x, y; mov.b64 x, {%1,%2}; mov.b64 y, {%3,%4}; st.relaxed.gpu.global.v2.b64 [%0], {x, y};}"
                 :: "l"(p), "r"(a), "r"(b), "r"(c), "r"(d) : "memory");
}
__device__ __forceinline__ void st_pub64(void* p, unsigned a, unsigned b) {
    asm volatile("{.reg .b64 x; mov.b64 x, {%1,%2}; st.relaxed.gpu.global.b64 [%0], x;}" :: "l"(p), "r"(a), "r"(b) : "memory");
}
__device__ __forceinline__ void st_pub1(void* p, unsigned a) {
    asm volatile("st.relaxed.gpu.global.u32 [%0], %1;" :: "l"(p), "r"(a) : "memory");
}
__device__ __forceinline__ unsigned tagw(unsigned w, unsigned tag) { return (w & ~1u) | tag; }
__device__ __forceinline__ unsigned tagf(float v, unsigned tag) { return (__float_as_uint(v) & ~1u) | tag; }
__device__ __forceinline__ float untagf(unsigned w) { return __uint_as_float(w & ~1u); }

__device__ __forceinline__ void mbar_wait(uint32_t bar) {
    uint32_t ok;
    int it = 0;
#pragma unroll 1
    do {
        asm volatile("{.reg .pred p; mbarrier.try_wait.parity.shared::cta.b64 p, [%1], 0; selp.u32 %0,1,0,p;}"
                     : "=r"(ok) : "r"(bar) : "memory");
    } while (!ok && ++it < SPIN_MAX);
}
__device__ __forceinline__ void bar_sync(int id, int n) { asm volatile("bar.sync %0, %1;" :: "r"(id), "r"(n) : "memory"); }
__device__ __forceinline__ void bar_arrive(int id, int n) { asm volatile("bar.arrive %0, %1;" :: "r"(id), "r"(n) : "memory"); }
__device__ __forceinline__ uint32_t mapa(uint32_t a, uint32_t rank) {
    uint32_t r;
    asm("mapa.shared::cluster.u32 %0, %1, %2;" : "=r"(r) : "r"(a), "r"(rank));
    return r;
}
__device__ __forceinline__ void st_async4(uint32_t a, float x, float y, float z, float w, uint32_t bar) {
    asm volatile("st.async.weak.shared::cluster.mbarrier::complete_tx::bytes.v4.f32 [%0], {%1,%2,%3,%4}, [%5];"
                 :: "r"(a), "f"(x), "f"(y), "f"(z), "f"(w), "r"(bar) : "memory");
}
__device__ __forceinline__ void st_async2(uint32_t a, uint32_t x, uint32_t y, uint32_t bar) {
    asm volatile("st.async.weak.shared::cluster.mbarrier::complete_tx::bytes.v2.b32 [%0], {%1,%2}, [%3];"
                 :: "r"(a), "r"(x), "r"(y), "r"(bar) : "memory");
}

__device__ __forceinline__ void ldsm4(uint32_t a, uint32_t (&r)[4]) {
    asm volatile("ldmatrix.sync.aligned.m8n8.x4.shared.b16 {%0,%1,%2,%3}, [%4];"
                 : "=r"(r[0]), "=r"(r[1]), "=r"(r[2]), "=r"(r[3]) : "r"(a) : "memory");
}
__device__ __forceinline__ void ldsm4t(uint32_t a, uint32_t (&r)[4]) {
    asm volatile("ldmatrix.sync.aligned.m8n8.x4.trans.shared.b16 {%0,%1,%2,%3}, [%4];"
                 : "=r"(r[0]), "=r"(r[1]), "=r"(r[2]), "=r"(r[3]) : "r"(a) : "memory");
}
__device__ __forceinline__ void mma(float (&c)[4], uint32_t a0, uint32_t a1, uint32_t a2, uint32_t a3, uint32_t b0, uint32_t b1) {
    asm("mma.sync.aligned.m16n8k16.row.col.f32.bf16.bf16.f32 {%0,%1,%2,%3}, {%4,%5,%6,%7}, {%8,%9}, {%0,%1,%2,%3};"
        : "+f"(c[0]), "+f"(c[1]), "+f"(c[2]), "+f"(c[3])
        : "r"(a0), "r"(a1), "r"(a2), "r"(a3), "r"(b0), "r"(b1));
}
__device__ __forceinline__ uint32_t pack_bf16(float lo, float hi) {
    uint32_t r;
    asm("cvt.rn.bf16x2.f32 %0, %1, %2;" : "=r"(r) : "f"(hi), "f"(lo));
    return r;
}
__device__ __forceinline__ float bf_lo(uint32_t w) { return __uint_as_float(w << 16); }
__device__ __forceinline__ float bf_hi(uint32_t w) { return __uint_as_float(w & 0xFFFF0000u); }
__device__ __forceinline__ float ex2(float x) { float y; asm("ex2.approx.ftz.f32 %0, %1;" : "=f"(y) : "f"(x)); return y; }
__device__ __forceinline__ uint4 lds128(uint32_t a) {
    uint4 v;
    asm volatile("ld.shared.v4.u32 {%0,%1,%2,%3}, [%4];" : "=r"(v.x), "=r"(v.y), "=r"(v.z), "=r"(v.w) : "r"(a) : "memory");
    return v;
}
__device__ __forceinline__ float2 lds64f(uint32_t a) {
    float2 v;
    asm volatile("ld.shared.v2.f32 {%0,%1}, [%2];" : "=f"(v.x), "=f"(v.y) : "r"(a) : "memory");
    return v;
}
__device__ __forceinline__ uint32_t lds32(uint32_t a) {
    uint32_t v;
    asm volatile("ld.shared.u32 %0, [%1];" : "=r"(v) : "r"(a) : "memory");
    return v;
}
__device__ __forceinline__ void sts128(uint32_t a, float x, float y, float z, float w) {
    asm volatile("st.shared.v4.f32 [%0], {%1,%2,%3,%4};" :: "r"(a), "f"(x), "f"(y), "f"(z), "f"(w) : "memory");
}
__device__ __forceinline__ void sts32(uint32_t a, uint32_t x) {
    asm volatile("st.shared.u32 [%0], %1;" :: "r"(a), "r"(x) : "memory");
}
__device__ __forceinline__ float warp_max(float v) {
    int k = __float_as_int(v);
    k ^= (k >> 31) & 0x7FFFFFFF;
    asm("redux.sync.max.s32 %0, %0, 0xffffffff;" : "+r"(k));
    k ^= (k >> 31) & 0x7FFFFFFF;
    return __int_as_float(k);
}

__device__ __forceinline__ void st_async1(uint32_t a, float x, uint32_t bar) {
    asm volatile("st.async.weak.shared::cluster.mbarrier::complete_tx::bytes.f32 [%0], %1, [%2];" :: "r"(a), "f"(x), "r"(bar) : "memory");
}
__device__ __forceinline__ uint32_t ldg32(const void* p) {
    uint32_t v;
    asm volatile("ld.global.nc.u32 %0, [%1];" : "=r"(v) : "l"(p));
    return v;
}
__device__ __forceinline__ void mma4(float (&c)[4], const uint32_t (&a)[4], uint32_t b0, uint32_t b1) { mma(c, a[0], a[1], a[2], a[3], b0, b1); }
__device__ __forceinline__ float shfl_x(float v, int m) { return __shfl_xor_sync(0xffffffffu, v, m); }
__device__ __forceinline__ unsigned chk(unsigned acc, unsigned w, unsigned tag) {
    unsigned d;
    asm("lop3.b32 %0, %1, %2, %3, 0xF6;" : "=r"(d) : "r"(acc), "r"(w), "r"(tag));
    return d;
}
__device__ __forceinline__ unsigned chk4(unsigned acc, const uint4& v, unsigned tag) { return chk(chk(chk(chk(acc, v.x, tag), v.y, tag), v.z, tag), v.w, tag); }
__device__ __forceinline__ void sts128u(uint32_t a, uint32_t x, uint32_t y, uint32_t z, uint32_t w) {
    asm volatile("st.shared.v4.u32 [%0], {%1,%2,%3,%4};" :: "r"(a), "r"(x), "r"(y), "r"(z), "r"(w) : "memory");
}
__device__ __forceinline__ uint32_t add_bf16x2(uint32_t a, uint32_t b) {
    uint32_t d;
    asm("add.rn.bf16x2 %0, %1, %2;" : "=r"(d) : "r"(a & ~1u), "r"(b & ~1u));
    return d;
}
__device__ __forceinline__ uint32_t fma_bf16x2(uint32_t a, uint32_t b, uint32_t c) {
    uint32_t d;
    asm("fma.rn.bf16x2 %0, %1, %2, %3;" : "=r"(d) : "r"(a), "r"(b), "r"(c));
    return d;
}
__device__ __forceinline__ uint32_t mul_bf16x2(uint32_t a, uint32_t b) {
    uint32_t d;
    asm("mul.rn.bf16x2 %0, %1, %2;" : "=r"(d) : "r"(a), "r"(b));
    return d;
}
__device__ __forceinline__ bool mbar_test(uint32_t bar) {
    uint32_t ok;
    asm volatile("{.reg .pred p; mbarrier.test_wait.parity.shared::cta.b64 p, [%1], 0; selp.u32 %0,1,0,p;}" : "=r"(ok) : "r"(bar) : "memory");
    return __all_sync(0xffffffffu, ok);
}
__device__ __forceinline__ uint4 ld_home4(const void* p) {
    uint4 v;
    asm volatile("{.reg .b128 d, z; .reg .b64 lo, hi; mov.b64 lo, 0; mov.b128 z, {lo, lo};"
                 " atom.relaxed.gpu.global.cas.b128 d, [%4], z, z; mov.b128 {lo, hi}, d; mov.b64 {%0,%1}, lo; mov.b64 {%2,%3}, hi;}"
                 : "=r"(v.x), "=r"(v.y), "=r"(v.z), "=r"(v.w) : "l"(p) : "memory");
    return v;
}
__device__ __forceinline__ uint2 ld_home2(const void* p) {
    uint2 v;
    asm volatile("{.reg .b64 a; atom.relaxed.gpu.global.or.b64 a, [%2], 0; mov.b64 {%0,%1}, a;}" : "=r"(v.x), "=r"(v.y) : "l"(p) : "memory");
    return v;
}
#define UNLIKELY(c) __builtin_expect(!!(c), 0)
#define PIN(x) asm volatile("" : "+r"(x))
#define PINL(x) asm volatile("" : "+l"(x))

__global__ void __cluster_dims__(2, 1, 1) __launch_bounds__(NTHREADS, 1)
fused_kernel(const __grid_constant__ Params P)
{
    extern __shared__ __align__(1024) unsigned char smem_raw[];
    const int tid = threadIdx.x;
    const int cl = blockIdx.x >> 1;
    const int r = blockIdx.x & 1;
    const uint32_t sm = (uint32_t)__cvta_generic_to_shared(smem_raw);
    unsigned t0 = 0;
    if (tid >= 256) t0 = gtimer();
    if (tid < 128) asm volatile("prefetch.global.L2 [%0];" :: "l"(P.wq + (size_t)(320 * r + tid) * 4096 + cl * 64));
    if (tid == 352) {
#pragma unroll
        for (int i = 0; i < 2; i++) asm volatile("mbarrier.init.shared::cta.b64 [%0], 1;" :: "r"(sm + SM_BAR + 8 * (B_WQ + i)) : "memory");
        asm volatile("fence.mbarrier_init.release.cluster;" ::: "memory");
#pragma unroll
        for (int i = 0; i < 2; i++) {
            asm volatile("mbarrier.arrive.expect_tx.shared::cta.b64 _, [%0], 20480;" :: "r"(sm + SM_BAR + 8 * (B_WQ + i)) : "memory");
            asm volatile("cp.async.bulk.tensor.3d.shared::cluster.global.mbarrier::complete_tx::bytes [%0], [%1, {%3,%4,%5}], [%2];"
                         :: "r"(sm + SM_WQ + i * 20480), "l"(&P.m[6]), "r"(sm + SM_BAR + 8 * (B_WQ + i)), "r"(0), "r"(320 * r + 160 * i), "r"(cl) : "memory");
        }
    }
    uint32_t xv[10], gw[10], old = 0;
    if ((tid >> 5) == 9) {
        const __nv_bfloat16* xp = P.x + 2 * (tid & 31);
        const __nv_bfloat16* gp = P.gate + 2 * (tid & 31);
#pragma unroll
        for (int i = 0; i < 10; i++) xv[i] = ldg32(xp + 64 * i);
        old = ld_poll1(&P.s->epoch);
#pragma unroll
        for (int i = 0; i < 10; i++) gw[i] = ldg32(gp + 64 * i);
    }
    int2 sched = make_int2(0, 0);
    if ((tid >> 5) == 8) sched = P.sched[tid & 31];
    PIN(sched.x); PIN(sched.y);
    if (tid == 320) {
#pragma unroll
        for (int i = 0; i < 6; i++) asm volatile("prefetch.tensormap [%0];" :: "l"(&P.m[i]) : "memory");
#pragma unroll
        for (int i = 0; i < NBAR; i++) asm volatile("mbarrier.init.shared::cta.b64 [%0], 1;" :: "r"(sm + SM_BAR + 8 * i) : "memory");
#pragma unroll
        for (int i = 0; i < B_DEAD; i++) {
            const uint32_t tx = i < B_CKV ? 8192 : i < B_W1 ? 16384 : i < B_WUV ? 10240 : i < B_WO ? 8192 : i < B_W2 ? 10240 : i == B_W2 ? 27648 :
                                i == B_SP ? 8192 : i == B_XC ? 2048 : i == B_XQ ? 1024 : i == B_FB ? 256 : 512;
            asm volatile("mbarrier.arrive.expect_tx.shared::cta.b64 _, [%0], %1;" :: "r"(sm + SM_BAR + 8 * i), "r"(tx) : "memory");
        }
        asm volatile("fence.mbarrier_init.release.cluster;" ::: "memory");
    }
    __syncwarp();
    asm volatile("barrier.cluster.arrive.relaxed.aligned;" ::: "memory");
    const int pu = cl < 36 ? cl - 4 : cl - 36, pn = cl < 36 ? 8 : 7;
    const int pv = pu >= 2 * pn ? pu - 2 * pn : pu;
    const int lc = cl < 4 ? cl : cl - pv + (pv >= pn ? 2 * (pv - pn) + 1 : 2 * pv);
    const int b = 2 * lc + r;
    const int h = b >> 2;
    const int pp = lc & 1;
    const int warp = tid >> 5, lane = tid & 31;
    const bool ffn = h < 27;
    Scratch* const S = P.s;

    if (warp < 8) {
        asm volatile("setmaxnreg.inc.sync.aligned.u32 208;");
        const int g = lane >> 2, t = lane & 3, l7 = lane & 7;
        const int kq = warp >> 1, nh = warp & 1;
        const uint32_t smp = mapa(sm, r ^ 1);
        const int row1 = 2 * l7 + ((lane >> 3) & 1);
        uint32_t a_wuk = sm + SM_WUK + (32 * warp + row1) * 128 + (((lane >> 4) ^ (row1 & 7)) << 4);
        unsigned* p_e2w = reinterpret_cast<unsigned*>(S->e2) + (((cl & 1) * 32 + (cl >> 1)) * 2 + r) * (4 * 32) + 16 * warp + 8 * (t & 1) + g;
        const uint4* p_e2r = S->e2 + ((16 * pp + (tid >> 4)) * 2 + r) * 32 + (tid & 15);
        uint32_t a_qsw = sm + SM_QS + (tid >> 4) * 512 + (((tid & 15) ^ ((tid >> 4) & 7)) << 4);
        uint32_t a_qsr = sm + SM_QS + (lane & 15) * 512 + (((lane >> 4) ^ l7) << 4);
        uint32_t a_s = sm + SM_CKV + (16 * warp + l7) * 128 + (((lane >> 3) ^ l7) << 4);
        uint32_t o_spw = warp * 1024 + ((lane ^ (nh << 2)) << 4);
        uint32_t a_ct = sm + SM_CKV + kq * 16384 + lane * 128 + (((4 * nh) ^ l7) << 4);
        uint32_t a_sr = sm + g * 1024 + ((warp ^ (g & 1)) << 6) + t * 16;
        uint2* p_stw = S->st + (16 * pp + 8 * r + warp) * 128 + h * 4 + lane;
        uint4* p_e3w = S->e3 + ((((16 * pp + g) * 2 + r) * 8 + warp) * 32 + h) * 4 + t;
        const uint4* p_e3r = S->e3 + ((h * 2 + r) * 8 + warp) * 128 + lane;
        const int krow = l7 + 8 * (lane >> 4), csel = (lane >> 3) & 1;
        uint32_t a_w1 = sm + SM_W1 + (80 * kq + krow) * 64 + (((2 * nh + csel) ^ (l7 >> 1)) << 4);
        uint32_t a_wuv = sm + SM_WUV + (32 * warp + krow) * 128 + ((csel ^ l7) << 4);
        uint32_t a_fin[5];
#pragma unroll
        for (int i = 0; i < 5; i++) {
            const int N = 10 * (warp & 3) + 2 * i + csel;
            a_fin[i] = sm + (warp >> 2) * 10240 + (N >> 3) * 2048 + krow * 128 + (((N & 7) ^ l7) << 4);
            PIN(a_fin[i]);
        }
        uint32_t b_xc = ((t >> 1) == r ? mapa(sm, r) : smp), b_xh = (nh == r ? mapa(sm, r) : smp);
        uint32_t a_xc = b_xc + SM_XC + (8 * r + warp) * 128 + ((t & 1) * 8 + g) * 8;
        uint32_t a_xh = b_xh + SM_XH + ((t & 1) * 8 + g) * 32 + (4 * r + kq) * 4;
        unsigned* p_e4w = reinterpret_cast<unsigned*>(S->e4) + (10 * warp + t) * (4 * 256) + b * 8 + g;
        PIN(a_wuk); PINL(p_e2w); PINL(p_e2r); PIN(a_s); PIN(a_qsw); PIN(a_qsr); PIN(o_spw); PIN(a_ct); PIN(a_sr);
        PINL(p_stw); PINL(p_e3w); PINL(p_e3r); PIN(a_w1); PIN(a_wuv); PIN(a_xc); PIN(a_xh); PINL(p_e4w);

        asm volatile("barrier.cluster.wait.aligned;" ::: "memory");
        bar_sync(1, 288);
        const unsigned tag = lds32(sm + SM_G + 4);
        t0 = lds32(sm + SM_G + 12);
        {
            uint32_t xb[10][2];
#pragma unroll
            for (int i = 0; i < 10; i++) {
                const uint32_t xa = sm + SM_XS + 160 * (warp >> 2) + 4 * t + 320 * (i / 5) + 32 * (i % 5);
                xb[i][0] = lds32(xa); xb[i][1] = lds32(xa + 16);
            }
            const uint32_t a_wq = sm + SM_WQ + (80 * (warp >> 2) + krow) * 128 + (((2 * (warp & 3) + csel) ^ l7) << 4);
            float c0[4] = {0.f, 0.f, 0.f, 0.f}, c1[4] = {0.f, 0.f, 0.f, 0.f};
#pragma unroll
            for (int i = 0; i < 2; i++) {
                mbar_wait(sm + SM_BAR + 8 * (B_WQ + i));
                uint32_t a[5][4];
#pragma unroll
                for (int j = 0; j < 5; j++) ldsm4t(a_wq + i * 20480 + j * 2048, a[j]);
#pragma unroll
                for (int j = 0; j < 5; j++) mma4((j & 1) ? c1 : c0, a[j], xb[5 * i + j][0], xb[5 * i + j][1]);
            }
            const uint32_t dst = (t & 2) ? smp : mapa(sm, r);
            st_async1(dst + SM_XQ + (2 * r + (warp >> 2)) * 256 + (16 * (warp & 3) + 8 * (t & 1) + g) * 4,
                      (t & 1) ? c0[2] + c1[2] : c0[0] + c1[0], dst + SM_BAR + 8 * B_XQ);
        }
        {
            mbar_wait(sm + SM_BAR + 8 * B_XQ);
            float2 qv[4];
#pragma unroll
            for (int i = 0; i < 4; i++) qv[i] = lds64f(sm + SM_XQ + i * 256 + lane * 8);
            qv[0].x = (qv[0].x + qv[1].x) + (qv[2].x + qv[3].x);
            qv[0].y = (qv[0].y + qv[1].y) + (qv[2].y + qv[3].y);
            const uint32_t qw = pack_bf16(qv[0].x, qv[0].y);
            uint32_t qb[8];
#pragma unroll
            for (int i = 0; i < 8; i++) qb[i] = __shfl_sync(0xffffffffu, qw, 4 * i + t);
            mbar_wait(sm + SM_BAR + 8 * (B_WUK + kq));
            uint32_t a[8][4];
#pragma unroll
            for (int s = 0; s < 8; s++) ldsm4((a_wuk ^ ((s & 3) << 5)) + (s >> 2) * 2048, a[s]);
            float c[4][4];
#pragma unroll
            for (int i = 0; i < 4; i++) {
                c[i][0] = c[i][1] = c[i][2] = c[i][3] = 0.f;
                mma4(c[i], a[2 * i], qb[4 * (i & 1)], qb[4 * (i & 1) + 1]);
            }
#pragma unroll
            for (int i = 0; i < 4; i++) mma4(c[i], a[2 * i + 1], qb[4 * (i & 1) + 2], qb[4 * (i & 1) + 3]);
            const float sc = 0.08838834764831845f * 1.4426950408889634f;
            const float lo = ((t & 1) ? c[2][0] + c[3][0] : c[0][0] + c[1][0]) * sc;
            const float hi = ((t & 1) ? c[2][2] + c[3][2] : c[0][2] + c[1][2]) * sc;
            const uint32_t lob = (lo != lo) ? 0x7FFEu : (((__float_as_uint(lo) + 0x10000u) >> 16) & 0xFFFEu);
            if (t < 2) st_pub1(p_e2w, (pack_bf16(0.f, hi) & 0xFFFF0000u) | lob | tag);
        }
        {
            bar_sync(3, 256);
            float s[4][4];
#pragma unroll
            for (int i = 0; i < 4; i++) s[i][0] = s[i][1] = s[i][2] = s[i][3] = 0.f;
            uint32_t ct[4][4][4];
            uint32_t bf[2][4][4];
            uint4 v[4];
#define LOAD_BF(q) _Pragma("unroll") for (int i = 0; i < 4; i++) ldsm4((a_s ^ ((i >> 1) << 6)) + (q) * 16384 + (i & 1) * 1024, bf[(q) & 1][i])
#define LOAD_CT()  _Pragma("unroll") for (int i = 0; i < 16; i++) ldsm4t((a_ct ^ ((i >> 2) << 4)) + (i & 3) * 4096, ct[i >> 2][i & 3])
#define STAGE_Q(st2) do { \
                int it = 0; \
                const unsigned tg = lds32(sm + SM_G + 4);     \
                if (UNLIKELY(chk4(chk4(0u, v[2 * (st2)], tg), v[2 * (st2) + 1], tg) & 1u)) { \
                    do { \
                        v[2 * (st2)] = ld_home4(p_e2r + (st2) * 16); \
                        v[2 * (st2) + 1] = ld_home4(p_e2r + (st2) * 16 + 64 * 32); \
                    } while ((chk4(chk4(0u, v[2 * (st2)], tag), v[2 * (st2) + 1], tag) & 1u) && ++it < SPIN_MAX); \
                } \
                const uint4 &x = v[2 * (st2)], &y = v[2 * (st2) + 1]; \
                sts128u(a_qsw + (st2) * 256, add_bf16x2(x.x, y.x), add_bf16x2(x.y, y.y), add_bf16x2(x.z, y.z), add_bf16x2(x.w, y.w)); \
            } while (0)
#define LOAD_QA(q) _Pragma("unroll") for (int i = 0; i < 4; i++) ldsm4((a_qsr ^ (i << 5)) + (q) * 128, qa[(q) & 1][i])
#define S_BLOCK(q) do { \
                const uint32_t (&A)[4][4] = qa[(q) & 1]; const uint32_t (&B)[4][4] = bf[(q) & 1]; \
                mma4(s[0], A[0], B[0][0], B[0][1]); mma4(s[1], A[0], B[1][0], B[1][1]); \
                mma4(s[2], A[1], B[0][2], B[0][3]); mma4(s[3], A[1], B[1][2], B[1][3]); \
                mma4(s[0], A[2], B[2][0], B[2][1]); mma4(s[1], A[2], B[3][0], B[3][1]); \
                mma4(s[2], A[3], B[2][2], B[2][3]); mma4(s[3], A[3], B[3][2], B[3][3]); \
            } while (0)
            uint32_t qa[2][4][4];
            { const unsigned lim = max((unsigned)P.ta, gtimer() - t0 + P.da); while (gtimer() - t0 < lim) {} }
            v[0] = ld_poll4(p_e2r);
            v[1] = ld_poll4(p_e2r + 64 * 32);
            mbar_wait(sm + SM_BAR + 8 * (B_CKV + 0));
            LOAD_BF(0);
            { const unsigned lim = max((unsigned)P.tb, gtimer() - t0 + P.db); while (gtimer() - t0 < lim) {} }
            asm volatile("cp.async.cg.shared.global [%0], [%1], 16;" :: "r"(sm + SM_SPL + tid * 16), "l"(p_e2r + 16) : "memory");
            asm volatile("cp.async.cg.shared.global [%0], [%1], 16;" :: "r"(sm + SM_SPL + 4096 + tid * 16), "l"(p_e2r + 16 + 64 * 32) : "memory");
            mbar_wait(sm + SM_BAR + 8 * (B_CKV + 1));
            LOAD_BF(1);
            if (kq < 2) { LOAD_CT(); }
            STAGE_Q(0);
            bar_sync(3, 256);
            LOAD_QA(0);
            LOAD_QA(1);
            S_BLOCK(0);
            S_BLOCK(1);
            mbar_wait(sm + SM_BAR + 8 * (B_CKV + 2));
            LOAD_BF(2);
            mbar_wait(sm + SM_BAR + 8 * (B_CKV + 3));
            LOAD_BF(3);
            asm volatile("cp.async.wait_all;" ::: "memory");
            v[2] = lds128(sm + SM_SPL + tid * 16);
            v[3] = lds128(sm + SM_SPL + 4096 + tid * 16);
            STAGE_Q(1);
            bar_sync(3, 256);
            LOAD_QA(2);
            LOAD_QA(3);
            S_BLOCK(2);
            S_BLOCK(3);
            {
                const float u0 = s[0][0] + s[2][0], u1 = s[0][1] + s[2][1], u2 = s[1][0] + s[3][0], u3 = s[1][1] + s[3][1];
                const float v0 = s[0][2] + s[2][2], v1 = s[0][3] + s[2][3], v2 = s[1][2] + s[3][2], v3 = s[1][3] + s[3][3];
                st_async4(smp + SM_SPR + o_spw, u0, u1, u2, u3, smp + SM_BAR + 8 * B_SP);
                st_async4(smp + SM_SPR + 512 + o_spw, v0, v1, v2, v3, smp + SM_BAR + 8 * B_SP);
                sts128(sm + SM_SPL + o_spw, u0, u1, u2, u3);
                sts128(sm + SM_SPL + 512 + o_spw, v0, v1, v2, v3);
            }
            if (kq >= 2) { LOAD_CT(); }
            bar_sync(2, 288);
            {
                const uint4 ul = lds128(a_sr + SM_SPL), vl = lds128(a_sr + SM_SPL + 512);
                mbar_wait(sm + SM_BAR + 8 * B_SP);
                const uint4 ur = lds128(a_sr + SM_SPR), vr = lds128(a_sr + SM_SPR + 512);
                const float u0 = __uint_as_float(ul.x) + __uint_as_float(ur.x), u1 = __uint_as_float(ul.y) + __uint_as_float(ur.y);
                const float u2 = __uint_as_float(ul.z) + __uint_as_float(ur.z), u3 = __uint_as_float(ul.w) + __uint_as_float(ur.w);
                const float v0 = __uint_as_float(vl.x) + __uint_as_float(vr.x), v1 = __uint_as_float(vl.y) + __uint_as_float(vr.y);
                const float v2 = __uint_as_float(vl.z) + __uint_as_float(vr.z), v3 = __uint_as_float(vl.w) + __uint_as_float(vr.w);
                const float mu = warp_max(fmaxf(fmaxf(u0, u1), fmaxf(u2, u3)));
                const float mv = warp_max(fmaxf(fmaxf(v0, v1), fmaxf(v2, v3)));
                const uint32_t a0 = pack_bf16(ex2(u0 - mu), ex2(u1 - mu)), a2 = pack_bf16(ex2(u2 - mu), ex2(u3 - mu));
                const uint32_t a1 = pack_bf16(ex2(v0 - mv), ex2(v1 - mv)), a3 = pack_bf16(ex2(v2 - mv), ex2(v3 - mv));
                sts128u(sm + SM_P + g * 512 + warp * 64 + t * 16, a0, a1, a2, a3);
                bar_sync(3, 256);
                uint4 pa[8];
#pragma unroll
                for (int q = 0; q < 8; q++) pa[q] = lds128(sm + SM_P + q * 512 + lane * 16);
                float o[2][4][4];
#pragma unroll
                for (int n = 0; n < 4; n++)
#pragma unroll
                    for (int e = 0; e < 4; e++) o[0][n][e] = o[1][n][e] = 0.f;
#pragma unroll
                for (int i = 0; i < 4; i++) {
#pragma unroll
                    for (int n = 0; n < 4; n++) mma(o[0][n], pa[2 * i].x, pa[2 * i].y, pa[2 * i].z, pa[2 * i].w, ct[n][i][0], ct[n][i][1]);
#pragma unroll
                    for (int n = 0; n < 4; n++) mma(o[1][n], pa[2 * i + 1].x, pa[2 * i + 1].y, pa[2 * i + 1].z, pa[2 * i + 1].w, ct[n][i][2], ct[n][i][3]);
                }
                const uint32_t q0 = r ? a1 : a0, q1 = r ? a3 : a2;
                float l = (bf_lo(q0) + bf_hi(q0)) + (bf_lo(q1) + bf_hi(q1));
#pragma unroll
                for (int d = 1; d < 32; d <<= 1) l += shfl_x(l, d);
                if (lane == 0) st_pub64(p_stw, tagf(l, tag), __float_as_uint(r ? mv : mu));
                uint32_t w0[4], w1[4];
#pragma unroll
                for (int n = 0; n < 4; n++) {
                    w0[n] = pack_bf16(o[0][n][0] + o[1][n][0], o[0][n][1] + o[1][n][1]);
                    w1[n] = pack_bf16(o[0][n][2] + o[1][n][2], o[0][n][3] + o[1][n][3]);
                }
                st_pub2x64(p_e3w, tagw(w0[0], tag), w0[1], tagw(w0[2], tag), w0[3]);
                st_pub2x64(p_e3w + 8 * 2 * 8 * 32 * 4, tagw(w1[0], tag), w1[1], tagw(w1[2], tag), w1[3]);
            }
        }
        if (ffn) {
            const uint32_t xa = sm + SM_XS + 160 * kq + 4 * t;
            uint32_t xf[5][2];
#pragma unroll
            for (int s = 0; s < 5; s++) { xf[s][0] = lds32(xa + s * 32); xf[s][1] = lds32(xa + s * 32 + 16); }
            mbar_wait(sm + SM_BAR + 8 * (B_W1 + (warp >> 2)));
            uint32_t aw[5][4];
#pragma unroll
            for (int s = 0; s < 5; s++) ldsm4t(a_w1 + s * 1024, aw[s]);
            float c0[4] = {0.f, 0.f, 0.f, 0.f}, c1[4] = {0.f, 0.f, 0.f, 0.f};
#pragma unroll
            for (int s = 0; s < 5; s++) mma4((s & 1) ? c1 : c0, aw[s], xf[s][0], xf[s][1]);
            if (t < 2) st_async1(a_xh, t ? c0[2] + c1[2] : c0[0] + c1[0], b_xh + SM_BAR + 8 * B_XH);
        }
        float invl;
        {
            uint32_t a[8][4];
            uint4 v[4];
            uint32_t fw[4];
            int it = 0;
            bar_sync(4, 288);
            {
                const unsigned tq = lds32(sm + SM_G + 16);
                while ((int)(gtimer() - tq) < 0) {}
            }
#pragma unroll
            for (int i = 0; i < 4; i++) v[i] = ld_poll2x64(p_e3r + i * 32);
            mbar_wait(sm + SM_BAR + 8 * (B_WUV + kq));
#pragma unroll
            for (int i = 0; i < 8; i++) ldsm4t((a_wuv ^ ((i >> 1) << 5)) + (i & 1) * 2048, a[i]);
            bar_sync(6, 288);
#pragma unroll
            for (int i = 0; i < 4; i++) fw[i] = lds32(sm + SM_F + (8 * i + g) * 4);
            invl = __uint_as_float(lds32(sm + SM_G + 8));
            {
                const unsigned tg = lds32(sm + SM_G + 4);
                unsigned bad = 0u;
#pragma unroll
                for (int i = 0; i < 4; i++) bad = chk(chk(bad, v[i].x, tg), v[i].z, tg);
                if (UNLIKELY(bad & 1u)) {
                    do {
                        bad = 0u;
#pragma unroll
                        for (int i = 0; i < 4; i++) v[i] = ld_home4(p_e3r + i * 32);
#pragma unroll
                        for (int i = 0; i < 4; i++) bad = chk(chk(bad, v[i].x, tag), v[i].z, tag);
                    } while ((bad & 1u) && ++it < SPIN_MAX);
                }
            }
            __syncwarp();
            uint32_t bx = mul_bf16x2(fw[0], v[0].x & ~1u), by = mul_bf16x2(fw[0], v[0].y), bz = mul_bf16x2(fw[0], v[0].z & ~1u), bw = mul_bf16x2(fw[0], v[0].w);
#pragma unroll
            for (int i = 1; i < 4; i++) {
                bx = fma_bf16x2(fw[i], v[i].x & ~1u, bx); by = fma_bf16x2(fw[i], v[i].y, by);
                bz = fma_bf16x2(fw[i], v[i].z & ~1u, bz); bw = fma_bf16x2(fw[i], v[i].w, bw);
            }
            float c[4][4];
#pragma unroll
            for (int i = 0; i < 4; i++) {
                c[i][0] = c[i][1] = c[i][2] = c[i][3] = 0.f;
                mma4(c[i], a[2 * i], bx, by);
            }
#pragma unroll
            for (int i = 0; i < 4; i++) mma4(c[i], a[2 * i + 1], bz, bw);
            float e[8], k4[4];
#pragma unroll
            for (int i = 0; i < 4; i++) { e[2 * i] = c[i][0] + c[i][1]; e[2 * i + 1] = c[i][2] + c[i][3]; }
            const bool t1 = t & 2, t0 = t & 1;
#pragma unroll
            for (int i = 0; i < 4; i++) k4[i] = (t1 ? e[4 + i] : e[i]) + shfl_x(t1 ? e[i] : e[4 + i], 2);
            const float k0 = (t0 ? k4[2] : k4[0]) + shfl_x(t0 ? k4[0] : k4[2], 1);
            const float k1 = (t0 ? k4[3] : k4[1]) + shfl_x(t0 ? k4[1] : k4[3], 1);
            st_async2(a_xc, __float_as_uint(k0), __float_as_uint(k1), b_xc + SM_BAR + 8 * B_XC);
        }
        const bool red = b < 80;
        const uint4* p_eh = S->eh + (27 * r + min(warp + 4 * g, 26)) * 8 + t;
        uint4 hv0, hv1;
        if (red && warp < 4) { hv0 = ld_poll4(p_eh); hv1 = ld_poll4(p_eh + 4); }
        {
            float c[5][4];
#pragma unroll
            for (int i = 0; i < 5; i++) c[i][0] = c[i][1] = c[i][2] = c[i][3] = 0.f;
            const int half = warp >> 2;
            const float gt = __uint_as_float(lds32(sm + SM_G));
            uint32_t wa[2][5][4];
            mbar_wait(sm + SM_BAR + 8 * (B_WO + half));
#pragma unroll
            for (int i = 0; i < 5; i++) ldsm4t(a_fin[i] + SM_WO, wa[0][i]);
            const bool early = mbar_test(sm + SM_BAR + 8 * (B_WO + 2 + half));
            if (early) {
#pragma unroll
                for (int i = 0; i < 5; i++) ldsm4t(a_fin[i] + SM_WO + 20480, wa[1][i]);
            }
            mbar_wait(sm + SM_BAR + 8 * B_XC);
            float xv[16];
#pragma unroll
            for (int i = 0; i < 16; i++) xv[i] = __uint_as_float(lds32(sm + SM_XC + i * 128 + lane * 4));
#pragma unroll
            for (int i = 0; i < 8; i++) xv[i] += xv[i + 8];
            const float cv = (((xv[0] + xv[4]) + (xv[1] + xv[5])) + ((xv[2] + xv[6]) + (xv[3] + xv[7]))) * (gt * invl);
            const uint32_t w = pack_bf16(cv, shfl_x(cv, 2));
            uint32_t bb[4];
#pragma unroll
            for (int q = 0; q < 4; q++) bb[q] = __shfl_sync(0xffffffffu, w, (q >> 1) * 16 + 4 * t + (q & 1));
#pragma unroll
            for (int i = 0; i < 5; i++) mma4(c[i], wa[0][i], bb[0], bb[1]);
            if (!early) {
                mbar_wait(sm + SM_BAR + 8 * (B_WO + 2 + half));
#pragma unroll
                for (int i = 0; i < 5; i++) ldsm4t(a_fin[i] + SM_WO + 20480, wa[1][i]);
            }
#pragma unroll
            for (int i = 0; i < 5; i++) mma4(c[i], wa[1][i], bb[2], bb[3]);
            const bool t0 = t & 1, t1 = t & 2;
            const float v0 = t1 ? (t0 ? c[1][2] : c[1][0]) : (t0 ? c[0][2] : c[0][0]);
            const float v1 = t1 ? (t0 ? c[3][2] : c[3][0]) : (t0 ? c[2][2] : c[2][0]);
            const float v2 = t0 ? c[4][2] : c[4][0];
            st_pub1(p_e4w, tagf(v0, tag));
            st_pub1(p_e4w + 4 * 4 * 256, tagf(v1, tag));
            if (!t1) st_pub1(p_e4w + 8 * 4 * 256, tagf(v2, tag));
        }
        if (red) {
            if (warp < 4) {
                int it = 0;
                if (UNLIKELY((chk4(0u, hv0, tag) | chk4(0u, hv1, tag)) & 1u)) {
                    do { hv0 = ld_home4(p_eh); hv1 = ld_home4(p_eh + 4); } while (((chk4(0u, hv0, tag) | chk4(0u, hv1, tag)) & 1u) && ++it < SPIN_MAX);
                }
                __syncwarp();
                const bool ok = warp + 4 * g < 27;
                const uint32_t w0 = ok ? pack_bf16(untagf(hv0.x), untagf(hv0.y)) : 0u, w1 = ok ? pack_bf16(untagf(hv0.z), untagf(hv0.w)) : 0u;
                const uint32_t w2 = ok ? pack_bf16(untagf(hv1.x), untagf(hv1.y)) : 0u, w3 = ok ? pack_bf16(untagf(hv1.z), untagf(hv1.w)) : 0u;
                uint32_t hb[14][2];
#pragma unroll
                for (int i = 0; i < 7; i++) {
                    hb[2 * i][0] = __shfl_sync(0xffffffffu, w0, 4 * i + t); hb[2 * i][1] = __shfl_sync(0xffffffffu, w1, 4 * i + t);
                    hb[2 * i + 1][0] = __shfl_sync(0xffffffffu, w2, 4 * i + t); hb[2 * i + 1][1] = __shfl_sync(0xffffffffu, w3, 4 * i + t);
                }
                const uint32_t a_w2 = sm + SM_W2 + (32 * warp + krow) * 32 + ((csel ^ (l7 >> 2)) << 4);
                const uint32_t a_w2l = a_w2 + (warp < 3 ? 6 * 4096 : 0);
                const uint32_t b_fb = ((t & 1) == r ? mapa(sm, r) : smp);
                mbar_wait(sm + SM_BAR + 8 * B_W2);
                uint32_t a[14][4];
#pragma unroll
                for (int i = 0; i < 12; i++) ldsm4t(a_w2 + (i >> 1) * 4096 + (i & 1) * 512, a[i]);
                ldsm4t(a_w2l, a[12]);
                ldsm4t(a_w2l + 512, a[13]);
                float c[4][4];
#pragma unroll
                for (int i = 0; i < 4; i++) c[i][0] = c[i][1] = c[i][2] = c[i][3] = 0.f;
#pragma unroll
                for (int i = 0; i < 14; i++) mma4(c[i & 3], a[i], hb[i][0], hb[i][1]);
                const float e = (t & 1) ? (c[0][2] + c[1][2]) + (c[2][2] + c[3][2]) : (c[0][0] + c[1][0]) + (c[2][0] + c[3][0]);
                if (t < 2) st_async1(b_fb + SM_FIN + g * 48 + 16 + (4 * r + warp) * 4, e, b_fb + SM_BAR + 8 * B_FB);
            } else {
                const uint4* p = S->e4 + b * 256 + (tid - 128);
                {
                    const unsigned now = gtimer();
                    const unsigned lim = now + max((int)(lds32(sm + SM_G + 16) + P.d4 - now), P.dc);
                    while ((int)(gtimer() - lim) < 0) {}
                }
                uint4 u, v;
                int it = 0;
                do { u = ld_poll4(p); v = ld_poll4(p + 128); } while (((chk4(0u, u, tag) | chk4(0u, v, tag)) & 1u) && ++it < SPIN_MAX);
                __syncwarp();
                const float s0 = untagf(u.x) + untagf(v.x), s1 = untagf(u.y) + untagf(v.y), s2 = untagf(u.z) + untagf(v.z), s3 = untagf(u.w) + untagf(v.w);
                const bool b4 = lane & 16, b3 = lane & 8;
                const float k0 = (b4 ? s2 : s0) + shfl_x(b4 ? s0 : s2, 16);
                const float k1 = (b4 ? s3 : s1) + shfl_x(b4 ? s1 : s3, 16);
                float s = (b3 ? k1 : k0) + shfl_x(b3 ? k0 : k1, 8);
                s += shfl_x(s, 4);
                s += shfl_x(s, 2);
                if (!(lane & 6)) sts32(sm + SM_FIN + ((lane & 1) * 4 + (lane >> 3)) * 48 + (warp - 4) * 4, __float_as_uint(s));
                bar_sync(7, 128);
                if (warp == 4 && lane < 8) {
                    mbar_wait(sm + SM_BAR + 8 * B_FB);
                    float o[3];
#pragma unroll
                    for (int i = 0; i < 3; i++) {
                        const uint4 u = lds128(sm + SM_FIN + lane * 48 + i * 16);
                        o[i] = (__uint_as_float(u.x) + __uint_as_float(u.y)) + (__uint_as_float(u.z) + __uint_as_float(u.w));
                    }
                    P.out[b * 8 + lane] = __float2bfloat16((o[1] + o[2]) + o[0]);
                    if (b == 0 && lane == 0) st_pub1(&S->epoch, tag);
                }
            }
        }
    } else {
        asm volatile("setmaxnreg.dec.sync.aligned.u32 88;");
        if (warp == 8) {
            const int k = lane;
            const uint32_t bar = sm + SM_BAR + 8 * min(k, B_W2);
            int map, c0 = 0, c1, c2;
            uint32_t dst, due;
            bool pending = true;
            if (k < B_CKV)      { map = 0; c1 = 256 * r + 64 * k;                c2 = cl;                dst = SM_WUK + k * 8192; }
            else if (k < B_W1)  { map = 1; c1 = 128 * h;                         c2 = 4 * r + k - B_CKV; dst = SM_CKV + (k - B_CKV) * 16384; }
            else if (k < B_WUV) { map = 2; c1 = 320 * r + 160 * (k - B_W1);      c2 = h; c0 = 32 * pp;   dst = SM_W1 + (k - B_W1) * 10240; pending = ffn; }
            else if (k < B_WO)  { map = 3; c1 = 256 * r + 64 * (k - B_WUV);      c2 = lc;                dst = SM_WUV + (k - B_WUV) * 8192; }
            else if (k < B_W2)  { map = 4; c1 = 32 * b + 16 * ((k - B_WO) >> 1); c2 = 5 * (k & 1);       dst = SM_WO + (k - B_WO) * 10240; }
            else                { map = 5; c1 = 864 * r + 216 * (k - B_W2);      c2 = lc >> 2; c0 = 16 * (lc & 3); dst = SM_W2 + (k - B_W2) * 6912; pending = b < 80 && k < NCHUNK; }
            const bool mine = pending;
            due = sched.x + ((b * 37) & 127) * sched.y / 128;
            int kc = min(k, B_W2) - 5, spins = 0;
            if (!ffn && (kc == B_W1 || kc == B_W1 + 1)) kc = B_W1 - 1;
            const uint32_t capbar = sm + SM_BAR + 8 * (kc >= 0 ? kc : B_WQ + (kc == -1));
            asm volatile("barrier.cluster.wait.aligned;" ::: "memory");
            int lim = B_WO;
            while (__any_sync(0xffffffffu, pending)) {
                if (!__any_sync(0xffffffffu, pending && k < lim)) {
                    if (lim == B_WO) { mbar_wait(sm + SM_BAR + 8 * B_XQ); lim = B_W2; }
                    else { mbar_wait(sm + SM_BAR + 8 * B_DEAD); lim = NCHUNK; }
                }
                bool go = pending && k < lim && gtimer() - t0 >= due;
                if (go) {
                    uint32_t ok;
                    asm volatile("{.reg .pred p; mbarrier.test_wait.parity.shared::cta.b64 p, [%1], 0; selp.u32 %0,1,0,p;}" : "=r"(ok) : "r"(capbar) : "memory");
                    go = ok || kc < -3 || ++spins > SPIN_MAX;
                }
                if (go) {
                    asm volatile("cp.async.bulk.tensor.3d.shared::cluster.global.mbarrier::complete_tx::bytes [%0], [%1, {%3,%4,%5}], [%2];"
                                 :: "r"(sm + dst), "l"(&P.m[map]), "r"(bar), "r"(c0), "r"(c1), "r"(c2) : "memory");
                    pending = false;
                }
            }
            if (mine && k >= B_WO) mbar_wait(bar);
            __syncwarp();
        } else if (warp == 11) {
            if (lane < 2) mbar_wait(sm + SM_BAR + 8 * (B_WQ + lane));
        } else if (warp == 10) {
            if (ffn) {
                mbar_wait(sm + SM_BAR + 8 * B_XH);
                const uint4 u = lds128(sm + SM_XH + (lane & 15) * 32), y = lds128(sm + SM_XH + (lane & 15) * 32 + 16);
                float hv = ((__uint_as_float(u.x) + __uint_as_float(u.y)) + (__uint_as_float(u.z) + __uint_as_float(u.w))) +
                           ((__uint_as_float(y.x) + __uint_as_float(y.y)) + (__uint_as_float(y.z) + __uint_as_float(y.w)));
                hv = bf_lo(pack_bf16(hv, 0.f));
                hv = __fdividef(hv, 1.f + __expf(-hv)) * (1.f - __uint_as_float(lds32(sm + SM_G)));
                if (lane < 16) st_pub1(reinterpret_cast<unsigned*>(S->eh) + 16 * b + 2 * (lane & 6) + 2 * (lane >> 3) + (lane & 1), tagf(hv, lds32(sm + SM_G + 4)));
            }
        } else if (warp == 9) {
            old &= 1u;
            st_pub64(S->st + (16 * pp + 8 * r + (lane >> 2)) * 128 + h * 4 + (lane & 3), old, 0u);
            if (lane == 0) { sts32(sm + SM_G + 4, old ^ 1u); sts32(sm + SM_G + 12, t0); }
            float z = 0.f;
#pragma unroll
            for (int i = 0; i < 10; i++) {
                if ((i >= 5) == (r != 0)) sts32(sm + SM_XS + ((i % 5) * 32 + lane) * 4, xv[i]);
                z = fmaf(bf_lo(xv[i]), bf_lo(gw[i]), z);
                z = fmaf(bf_hi(xv[i]), bf_hi(gw[i]), z);
            }
#pragma unroll
            for (int d = 1; d < 32; d <<= 1) z += shfl_x(z, d);
            if (lane == 0) sts32(sm + SM_G, __float_as_uint(__fdividef(1.f, 1.f + __expf(-z))));
            bar_arrive(1, 288);
            {
                bar_sync(2, 288);
                if (lane == 0) asm volatile("mbarrier.arrive.shared::cta.b64 _, [%0];" :: "r"(sm + SM_BAR + 8 * B_DEAD) : "memory");
                mbar_wait(sm + SM_BAR + 8 * B_SP);
                const unsigned now = gtimer();
                if (lane < 8) st_pub64(S->st + (16 * pp + 8 * r + lane) * 128 + h * 4 + 1, (now & ~1u) | (old ^ 1u), 0u);
                const uint2* p_str = S->st + h * 128 + lane * 4;
                while (gtimer() - now < P.d3) {}
                uint2 st;
                int it = 0;
                do { st = ld_home2(p_str + 1); } while (!__all_sync(0xffffffffu, (st.x ^ old) & 1u) && ++it < SPIN_MAX);
                const unsigned tmax = now + (unsigned)min(__reduce_max_sync(0xffffffffu, (int)(st.x - now)), 100000);
                if (lane == 0) sts32(sm + SM_G + 16, tmax + P.d5);
                bar_arrive(4, 288);
                while ((int)(gtimer() - (tmax + P.d6)) < 0) {}
                st = ld_home2(p_str);
                while (!__all_sync(0xffffffffu, (st.x ^ old) & 1u) && ++it < SPIN_MAX) st = ld_home2(p_str);
                const float M = warp_max(__uint_as_float(st.y));
                const float ff = ex2(__uint_as_float(st.y) - M);
                const uint32_t f2 = pack_bf16(ff, ff);
                sts32(sm + SM_F + lane * 4, f2);
                float L = bf_lo(f2) * untagf(st.x);
#pragma unroll
                for (int d = 1; d < 32; d <<= 1) L += shfl_x(L, d);
                if (lane == 0) sts32(sm + SM_G + 8, __float_as_uint(__fdividef(1.f, L)));
                bar_arrive(6, 288);
            }
        }
    }
}

typedef CUresult (*EncodeFn)(CUtensorMap*, CUtensorMapDataType, cuuint32_t, void*, const cuuint64_t*, const cuuint64_t*,
                             const cuuint32_t*, const cuuint32_t*, CUtensorMapInterleave, CUtensorMapSwizzle,
                             CUtensorMapL2promotion, CUtensorMapFloatOOBfill);

void make_map(EncodeFn enc, CUtensorMap* m, const void* base, int rows, int cols, int box_cols, int box_rows, int box_blks) {
    cuuint64_t gd[3] = {64, (cuuint64_t)rows, (cuuint64_t)(cols / 64)};
    cuuint64_t gs[2] = {(cuuint64_t)cols * 2, 128};
    cuuint32_t bd[3] = {(cuuint32_t)box_cols, (cuuint32_t)box_rows, (cuuint32_t)box_blks};
    cuuint32_t es[3] = {1, 1, 1};
    enc(m, CU_TENSOR_MAP_DATA_TYPE_BFLOAT16, 3, const_cast<void*>(base), gd, gs, bd, es, CU_TENSOR_MAP_INTERLEAVE_NONE,
        box_cols == 64 ? CU_TENSOR_MAP_SWIZZLE_128B : box_cols == 32 ? CU_TENSOR_MAP_SWIZZLE_64B : CU_TENSOR_MAP_SWIZZLE_32B,
        CU_TENSOR_MAP_L2_PROMOTION_NONE, CU_TENSOR_MAP_FLOAT_OOB_FILL_NONE);
}

}

extern "C" void kernel_launch(void* const* d_in, const int* in_sizes, int n_in, void* d_out, int out_size) {
    (void)in_sizes; (void)n_in; (void)out_size;
    static EncodeFn enc = nullptr;
    static Scratch* scratch = nullptr;
    if (!enc) {
        void* fn = nullptr;
        cudaDriverEntryPointQueryResult st;
        cudaGetDriverEntryPoint("cuTensorMapEncodeTiled", &fn, cudaEnableDefault, &st);
        enc = (EncodeFn)fn;
        cudaFuncSetAttribute(fused_kernel, cudaFuncAttributeMaxDynamicSharedMemorySize, SMEM_BYTES);
        cudaGetSymbolAddress((void**)&scratch, g_s);
    }
    Params p;
    make_map(enc, &p.m[0], d_in[3], 512, 4096, 64, 64, 1);
    make_map(enc, &p.m[1], d_in[1], 4096, 512, 64, 128, 1);
    make_map(enc, &p.m[2], d_in[7], 640, 1728, 32, 160, 1);
    make_map(enc, &p.m[3], d_in[4], 512, 4096, 64, 64, 1);
    make_map(enc, &p.m[4], d_in[5], 4096, 640, 64, 16, 5);
    make_map(enc, &p.m[5], d_in[8], 1728, 640, 16, 216, 1);
    make_map(enc, &p.m[6], d_in[2], 640, 4096, 64, 160, 1);
    p.x = (const __nv_bfloat16*)d_in[0];
    p.wq = (const __nv_bfloat16*)d_in[2];
    p.gate = (const __nv_bfloat16*)d_in[9];
    p.out = (__nv_bfloat16*)d_out;
    p.s = scratch;
    static const int gap[NCHUNK] = {1370, 310, 220, 225, 560, 280, 348, 274, 373, 273, 262, 150, 340, 515, 283, 251, 554, 479, 547, 50, 113, 101};
    for (int i = 0, t = 0; i < 32; i++) {
        t += i < NCHUNK ? gap[i] : 0;
        p.sched[i].x = t;
        p.sched[i].y = i < 4 ? 45 : i < NCHUNK - 3 ? 405 : 365;
    }
    p.ta = 4050;
    p.tb = 4240;
    p.da = 250;
    p.db = 50;
    p.d3 = 300;
    p.d5 = 1230;
    p.d6 = 800;
    p.d4 = 1900;
    p.dc = 50;
    fused_kernel<<<NCTA, NTHREADS, SMEM_BYTES>>>(p);
}
```
